```python
import torch

def _softmax(x, axis=-1):
    return torch.softmax(x, dim=axis)
def _gelu(x):
    return torch.nn.functional.gelu(x, approximate="tanh")
def _silu(x):
    return torch.nn.functional.silu(x)
def _sigmoid(x):
    return torch.sigmoid(x)
def _layernorm(x, axis=-1, eps=1e-5):
    m = x.mean(dim=axis, keepdim=True)
    v = x.var(dim=axis, keepdim=True, unbiased=False)
    return (x - m) / torch.sqrt(v + eps)
def _scatter_add(tgt, idx, src, axis=0):
    return tgt.clone().index_add_(axis, idx, src)
def _segment_sum(src, seg, n):
    out = torch.zeros((n,) + src.shape[1:], dtype=src.dtype)
    return out.index_add_(0, seg, src)
def _pad(x, pw):
    flat = tuple(v for pair in reversed(pw) for v in pair)
    return torch.nn.functional.pad(x, flat)

kernel_name = 'gated_mix__linear_kernel_hedgehog__compressed_kv_cla__prompt'

def setup_inputs():

    _w = (lambda a: (lambda t: t.to(torch.bfloat16) if t.is_floating_point() else t)(torch.as_tensor(a)))
    def _A_setup():
        B, S, D, H = 1, 2048, 1024, 32
        Dh = D // H
        return {
            "x": _w((lambda *s: torch.randn(*s, dtype=torch.bfloat16) * 0.05)(B, S, D)),
            "wqkv": _w((lambda *s: torch.randn(*s, dtype=torch.bfloat16) * 1.6)(D, 3 * D)),
            "w_phi": _w((lambda *s: torch.randn(*s, dtype=torch.bfloat16) * 1.6)(H, Dh, Dh) * (Dh ** -0.5)),
            "wo": _w((lambda *s: torch.randn(*s, dtype=torch.bfloat16) * 0.05)(D, D)),
        }
    _A_in = _A_setup()

    def _B_setup():
        B, H, Sq, Sk, D, M = 1, 32, 2048, 2048, 128, 1024
        Dc = 4 * D
        return {
            "x": _w((lambda *s: torch.randn(*s, dtype=torch.bfloat16) * 0.05)(B, Sq, M)),
            "c_kv": _w((lambda *s: torch.randn(*s, dtype=torch.bfloat16) * 0.8)(B, Sk, Dc)),
            "w_q": _w((lambda *s: torch.randn(*s, dtype=torch.bfloat16) * 6.4)(M, H, D) * (M ** -0.5)),
            "w_uk": _w((lambda *s: torch.randn(*s, dtype=torch.bfloat16) * 6.4)(Dc, H, D) * (Dc ** -0.5)),
            "w_uv": _w((lambda *s: torch.randn(*s, dtype=torch.bfloat16) * 0.8)(Dc, H, D) * (Dc ** -0.5)),
            "w_o": _w((lambda *s: torch.randn(*s, dtype=torch.bfloat16) * 0.8)(H, D, M) * ((H * D) ** -0.5)),
        }
    _B_in = _B_setup()

    return {
        "A_x": _A_in["x"],
        "A_wqkv": _A_in["wqkv"],
        "A_w_phi": _A_in["w_phi"],
        "A_wo": _A_in["wo"],
        "B_x": _B_in["x"],
        "B_c_kv": _B_in["c_kv"],
        "B_w_q": _B_in["w_q"],
        "B_w_uk": _B_in["w_uk"],
        "B_w_uv": _B_in["w_uv"],
        "B_w_o": _B_in["w_o"],
        "gate_w": _w((lambda *s: torch.randn(*s, dtype=torch.bfloat16) * 0.05)(1024) * 16.0),
    }

def reference(A_x, A_wqkv, A_w_phi, A_wo, B_x, B_c_kv, B_w_q, B_w_uk, B_w_uv, B_w_o, gate_w):
    def _A_ref(x, wqkv, w_phi, wo):
        B, S, D = x.shape
        H = 32; Dh = D // H
        qkv = (lambda x, *d: x.permute(*d))((x @ wqkv).reshape(B, S, 3, H, Dh), 2, 0, 3, 1, 4)
        q, k, v = qkv[0], qkv[1], qkv[2]
        pq = torch.einsum("bhsd,hdf->bhsf", q, w_phi)
        pk = torch.einsum("bhsd,hdf->bhsf", k, w_phi)
        phi_q = torch.concatenate([_softmax(pq, axis=-1), _softmax(-pq, axis=-1)], axis=-1)
        phi_k = torch.concatenate([_softmax(pk, axis=-1), _softmax(-pk, axis=-1)], axis=-1)
        kv = torch.einsum("bhsf,bhsd->bhfd", phi_k, v)
        z  = torch.einsum("bhsf->bhf", phi_k)
        num = torch.einsum("bhqf,bhfd->bhqd", phi_q, kv)
        den = torch.einsum("bhqf,bhf->bhq", phi_q, z)[..., None] + 1e-6
        o = num / den
        return (lambda x, *d: x.permute(*d))(o, 0, 2, 1, 3).reshape(B, S, D) @ wo

    def _B_ref(x, c_kv, w_q, w_uk, w_uv, w_o):
        B, Sq, M = x.shape[0], x.shape[1], x.shape[2]
        Sk = c_kv.shape[1]
        H, D = w_q.shape[1], w_q.shape[2]
        q = torch.einsum("bqm,mhd->bhqd", x, w_q)
        k = torch.einsum("bkc,chd->bhkd", c_kv, w_uk)
        v = torch.einsum("bkc,chd->bhkd", c_kv, w_uv)
        scores = torch.einsum("bhqd,bhkd->bhqk", q, k) * (D ** -0.5)
        off = Sk - Sq
        qi = torch.arange(Sq)[:, None]
        kj = torch.arange(Sk)[None, :]
        cmask = kj <= (qi + off)
        scores = torch.where(cmask[None, None], scores, -1e9)
        p = _softmax(scores, axis=-1)
        ctx = torch.einsum("bhqk,bhkd->bhqd", p, v)
        return torch.einsum("bhqd,hdm->bqm", ctx, w_o)

    x = A_x
    g = _sigmoid((x * gate_w).sum(-1, keepdims=True))
    a = _A_ref(x, A_wqkv, A_w_phi, A_wo)
    b = _B_ref(x, B_c_kv, B_w_q, B_w_uk, B_w_uv, B_w_o)
    return g * a + (1 - g) * b
```

```cpp
#include <cuda_runtime.h>
#include <cuda_bf16.h>
#include <cuda.h>
#include <stdint.h>

#define SEQ 2048
#define NHEAD 32

__device__ __align__(1024) __nv_bfloat16 g_qkv[(size_t)3 * NHEAD * SEQ * 128];
__device__ __align__(1024) __nv_bfloat16 g_a3[(size_t)SEQ * 5120];
__device__ __align__(1024) float g_part[(size_t)NHEAD * 32 * 2112];
__device__ __align__(1024) uint32_t g_kvfrag[NHEAD * 10 * 32 * 4];
__device__ float g_gate[SEQ];
__device__ unsigned g_cnt[16];

__device__ __forceinline__ uint32_t smem_u32(const void* p) { return (uint32_t)__cvta_generic_to_shared(p); }
__device__ __forceinline__ void mbar_init(uint32_t bar, uint32_t cnt) {
  asm volatile("mbarrier.init.shared::cta.b64 [%0], %1;" ::"r"(bar), "r"(cnt) : "memory");
}
__device__ __forceinline__ void mbar_expect_tx(uint32_t bar, uint32_t bytes) {
  asm volatile("mbarrier.arrive.expect_tx.shared::cta.b64 _, [%0], %1;" ::"r"(bar), "r"(bytes) : "memory");
}
__device__ __forceinline__ void mbar_arrive(uint32_t bar) {
  asm volatile("mbarrier.arrive.shared::cta.b64 _, [%0];" ::"r"(bar) : "memory");
}
__device__ __forceinline__ void mbar_arrive_cluster(uint32_t bar, uint32_t cta) {
  asm volatile(
      "{\n.reg .b32 ra;\nmapa.shared::cluster.u32 ra, %0, %1;\n"
      "mbarrier.arrive.shared::cluster.b64 _, [ra];\n}\n" ::"r"(bar), "r"(cta)
      : "memory");
}
__device__ __forceinline__ bool mbar_try(uint32_t bar, uint32_t parity) {
  uint32_t ok;
  asm volatile(
      "{\n.reg .pred p;\nmbarrier.try_wait.parity.shared::cta.b64 p, [%1], %2;\nselp.u32 %0, 1, 0, p;\n}\n"
      : "=r"(ok)
      : "r"(bar), "r"(parity)
      : "memory");
  return ok != 0;
}
__device__ __forceinline__ void mbar_wait(uint32_t bar, uint32_t parity) {
  if (mbar_try(bar, parity)) return;
  uint32_t n = 0;
  while (!mbar_try(bar, parity)) {
    if (++n > (1u << 22)) __trap();
  }
}
__device__ __forceinline__ bool mbar_try_cluster(uint32_t bar, uint32_t parity) {
  uint32_t ok;
  asm volatile(
      "{\n.reg .pred p;\nmbarrier.try_wait.parity.acquire.cluster.shared::cta.b64 p, [%1], %2;\nselp.u32 %0, 1, 0, p;\n}\n"
      : "=r"(ok)
      : "r"(bar), "r"(parity)
      : "memory");
  return ok != 0;
}
__device__ __forceinline__ void mbar_wait_cluster(uint32_t bar, uint32_t parity) {
  uint32_t n = 0;
  while (!mbar_try_cluster(bar, parity)) {
    if (++n > (1u << 22)) __trap();
  }
}
__device__ __forceinline__ void tma_load(uint32_t dst, const CUtensorMap* m, int x, int y, uint32_t bar) {
  asm volatile(
      "cp.async.bulk.tensor.2d.shared::cluster.global.mbarrier::complete_tx::bytes [%0], [%1, {%3, %4}], [%2];" ::"r"(dst),
      "l"(m), "r"(bar), "r"(x), "r"(y)
      : "memory");
}
__device__ __forceinline__ void tma_load_mc(uint32_t dst, const CUtensorMap* m, int x, int y, uint32_t bar, uint16_t mask) {
  asm volatile(
      "cp.async.bulk.tensor.2d.shared::cluster.global.mbarrier::complete_tx::bytes.multicast::cluster [%0], [%1, {%3, "
      "%4}], [%2], %5;" ::"r"(dst),
      "l"(m), "r"(bar), "r"(x), "r"(y), "h"(mask)
      : "memory");
}
__device__ __forceinline__ void tma_store(const CUtensorMap* m, uint32_t src, int x, int y) {
  asm volatile("cp.async.bulk.tensor.2d.global.shared::cta.bulk_group [%0, {%2, %3}], [%1];" ::"l"(m), "r"(src), "r"(x),
               "r"(y)
               : "memory");
}
__device__ __forceinline__ void tma_prefetch_desc(const CUtensorMap* m) {
  asm volatile("prefetch.tensormap [%0];" ::"l"(m) : "memory");
}
__device__ __forceinline__ void bulk_commit() { asm volatile("cp.async.bulk.commit_group;" ::: "memory"); }
template <int N>
__device__ __forceinline__ void bulk_wait_read() {
  asm volatile("cp.async.bulk.wait_group.read %0;" ::"n"(N) : "memory");
}
template <int N>
__device__ __forceinline__ void bulk_wait() {
  asm volatile("cp.async.bulk.wait_group %0;" ::"n"(N) : "memory");
}
__device__ __forceinline__ void fence_async_smem() { asm volatile("fence.proxy.async.shared::cta;" ::: "memory"); }
__device__ __forceinline__ void wg_fence() { asm volatile("wgmma.fence.sync.aligned;" ::: "memory"); }
__device__ __forceinline__ void wg_commit() { asm volatile("wgmma.commit_group.sync.aligned;" ::: "memory"); }
template <int N>
__device__ __forceinline__ void wg_wait() {
  asm volatile("wgmma.wait_group.sync.aligned %0;" ::"n"(N) : "memory");
}
template <int N>
__device__ __forceinline__ void reg_fence(float (&d)[N]) {
#pragma unroll
  for (int i = 0; i < N; i++) asm volatile("" : "+f"(d[i])::"memory");
}
template <int N>
__device__ __forceinline__ void reg_undef(float (&d)[N]) {
#pragma unroll
  for (int i = 0; i < N; i++) asm volatile("" : "=f"(d[i]));
}
template <int N>
__device__ __forceinline__ void reg_fence_u(uint32_t (&d)[N]) {
#pragma unroll
  for (int i = 0; i < N; i++) asm volatile("" : "+r"(d[i])::"memory");
}
__device__ __forceinline__ void bar_sync(int id, int n) { asm volatile("bar.sync %0, %1;" ::"r"(id), "r"(n) : "memory"); }
__device__ __forceinline__ void bar_arrive(int id, int n) { asm volatile("bar.arrive %0, %1;" ::"r"(id), "r"(n) : "memory"); }
__device__ __forceinline__ void cluster_arrive() { asm volatile("barrier.cluster.arrive.release.aligned;" ::: "memory"); }
__device__ __forceinline__ void cluster_wait() { asm volatile("barrier.cluster.wait.acquire.aligned;" ::: "memory"); }
__device__ __forceinline__ uint32_t cluster_rank() {
  uint32_t r;
  asm volatile("mov.u32 %0, %%cluster_ctarank;" : "=r"(r));
  return r;
}
__device__ __forceinline__ void pdl_wait() { asm volatile("griddepcontrol.wait;" ::: "memory"); }
__device__ __forceinline__ void pdl_launch() { asm volatile("griddepcontrol.launch_dependents;" ::: "memory"); }
template <int N>
__device__ __forceinline__ void reg_dec() {
  asm volatile("setmaxnreg.dec.sync.aligned.u32 %0;" ::"n"(N));
}
template <int N>
__device__ __forceinline__ void reg_inc() {
  asm volatile("setmaxnreg.inc.sync.aligned.u32 %0;" ::"n"(N));
}
__device__ __forceinline__ uint32_t pack_bf16(float lo, float hi) {
  uint32_t r;
  asm("cvt.rn.bf16x2.f32 %0, %1, %2;" : "=r"(r) : "f"(hi), "f"(lo));
  return r;
}
__device__ __forceinline__ float ex2(float x) {
  float y;
  asm("ex2.approx.ftz.f32 %0, %1;" : "=f"(y) : "f"(x));
  return y;
}
__device__ __forceinline__ float rcp(float x) {
  float y;
  asm("rcp.approx.ftz.f32 %0, %1;" : "=f"(y) : "f"(x));
  return y;
}
__device__ __forceinline__ void stsm4(uint32_t addr, uint32_t r0, uint32_t r1, uint32_t r2, uint32_t r3) {
  asm volatile("stmatrix.sync.aligned.m8n8.x4.shared.b16 [%0], {%1, %2, %3, %4};" ::"r"(addr), "r"(r0), "r"(r1), "r"(r2),
               "r"(r3)
               : "memory");
}
__device__ __forceinline__ void mma16816(float (&d)[4], uint32_t a0, uint32_t a1, uint32_t a2, uint32_t a3, uint32_t b0,
                                         uint32_t b1) {
  asm volatile(
      "mma.sync.aligned.m16n8k16.row.col.f32.bf16.bf16.f32 {%0,%1,%2,%3}, {%4,%5,%6,%7}, {%8,%9}, {%0,%1,%2,%3};"
      : "+f"(d[0]), "+f"(d[1]), "+f"(d[2]), "+f"(d[3])
      : "r"(a0), "r"(a1), "r"(a2), "r"(a3), "r"(b0), "r"(b1));
}
__device__ __forceinline__ unsigned ld_acquire(const unsigned* p) {
  unsigned v;
  asm volatile("ld.acquire.gpu.global.u32 %0, [%1];" : "=r"(v) : "l"(p) : "memory");
  return v;
}
__device__ __forceinline__ void spin_until(const unsigned* p, unsigned target) {
  uint32_t n = 0;
  while (ld_acquire(p) < target) {
    __nanosleep(64);
    if (++n > (1u << 24)) __trap();
  }
}
__device__ __forceinline__ void red_release(unsigned* p, unsigned v) {
  asm volatile("red.release.gpu.global.add.u32 [%0], %1;" ::"l"(p), "r"(v) : "memory");
}
__device__ __forceinline__ uint64_t make_desc(uint32_t addr, uint32_t lbo, uint32_t sbo) {
  return (uint64_t)((addr & 0x3FFFF) >> 4) | ((uint64_t)(lbo >> 4) << 16) | ((uint64_t)(sbo >> 4) << 32) | (1ull << 62);
}

__device__ __forceinline__ void wgmma_n256_ss_tb_z(float (&d)[128], uint64_t da, uint64_t db) {
  asm volatile("{\n"
    "wgmma.mma_async.sync.aligned.m64n256k16.f32.bf16.bf16 "
    "{%0, %1, %2, %3, %4, %5, %6, %7, %8, %9, %10, %11, %12, %13, %14, %15, "
    "%16, %17, %18, %19, %20, %21, %22, %23, %24, %25, %26, %27, %28, %29, %30, %31, "
    "%32, %33, %34, %35, %36, %37, %38, %39, %40, %41, %42, %43, %44, %45, %46, %47, "
    "%48, %49, %50, %51, %52, %53, %54, %55, %56, %57, %58, %59, %60, %61, %62, %63, "
    "%64, %65, %66, %67, %68, %69, %70, %71, %72, %73, %74, %75, %76, %77, %78, %79, "
    "%80, %81, %82, %83, %84, %85, %86, %87, %88, %89, %90, %91, %92, %93, %94, %95, "
    "%96, %97, %98, %99, %100, %101, %102, %103, %104, %105, %106, %107, %108, %109, %110, %111, "
    "%112, %113, %114, %115, %116, %117, %118, %119, %120, %121, %122, %123, %124, %125, %126, %127}, "
    "%128, %129, 0, 1, 1, 0, 1;\n}\n"
    : "=f"(d[0]), "=f"(d[1]), "=f"(d[2]), "=f"(d[3]), "=f"(d[4]), "=f"(d[5]), "=f"(d[6]), "=f"(d[7]),
      "=f"(d[8]), "=f"(d[9]), "=f"(d[10]), "=f"(d[11]), "=f"(d[12]), "=f"(d[13]), "=f"(d[14]), "=f"(d[15]),
      "=f"(d[16]), "=f"(d[17]), "=f"(d[18]), "=f"(d[19]), "=f"(d[20]), "=f"(d[21]), "=f"(d[22]), "=f"(d[23]),
      "=f"(d[24]), "=f"(d[25]), "=f"(d[26]), "=f"(d[27]), "=f"(d[28]), "=f"(d[29]), "=f"(d[30]), "=f"(d[31]),
      "=f"(d[32]), "=f"(d[33]), "=f"(d[34]), "=f"(d[35]), "=f"(d[36]), "=f"(d[37]), "=f"(d[38]), "=f"(d[39]),
      "=f"(d[40]), "=f"(d[41]), "=f"(d[42]), "=f"(d[43]), "=f"(d[44]), "=f"(d[45]), "=f"(d[46]), "=f"(d[47]),
      "=f"(d[48]), "=f"(d[49]), "=f"(d[50]), "=f"(d[51]), "=f"(d[52]), "=f"(d[53]), "=f"(d[54]), "=f"(d[55]),
      "=f"(d[56]), "=f"(d[57]), "=f"(d[58]), "=f"(d[59]), "=f"(d[60]), "=f"(d[61]), "=f"(d[62]), "=f"(d[63]),
      "=f"(d[64]), "=f"(d[65]), "=f"(d[66]), "=f"(d[67]), "=f"(d[68]), "=f"(d[69]), "=f"(d[70]), "=f"(d[71]),
      "=f"(d[72]), "=f"(d[73]), "=f"(d[74]), "=f"(d[75]), "=f"(d[76]), "=f"(d[77]), "=f"(d[78]), "=f"(d[79]),
      "=f"(d[80]), "=f"(d[81]), "=f"(d[82]), "=f"(d[83]), "=f"(d[84]), "=f"(d[85]), "=f"(d[86]), "=f"(d[87]),
      "=f"(d[88]), "=f"(d[89]), "=f"(d[90]), "=f"(d[91]), "=f"(d[92]), "=f"(d[93]), "=f"(d[94]), "=f"(d[95]),
      "=f"(d[96]), "=f"(d[97]), "=f"(d[98]), "=f"(d[99]), "=f"(d[100]), "=f"(d[101]), "=f"(d[102]), "=f"(d[103]),
      "=f"(d[104]), "=f"(d[105]), "=f"(d[106]), "=f"(d[107]), "=f"(d[108]), "=f"(d[109]), "=f"(d[110]), "=f"(d[111]),
      "=f"(d[112]), "=f"(d[113]), "=f"(d[114]), "=f"(d[115]), "=f"(d[116]), "=f"(d[117]), "=f"(d[118]), "=f"(d[119]),
      "=f"(d[120]), "=f"(d[121]), "=f"(d[122]), "=f"(d[123]), "=f"(d[124]), "=f"(d[125]), "=f"(d[126]), "=f"(d[127])
    : "l"(da), "l"(db));
}
__device__ __forceinline__ void wgmma_n256_ss_tb(float (&d)[128], uint64_t da, uint64_t db) {
  asm volatile("{\n"
    "wgmma.mma_async.sync.aligned.m64n256k16.f32.bf16.bf16 "
    "{%0, %1, %2, %3, %4, %5, %6, %7, %8, %9, %10, %11, %12, %13, %14, %15, "
    "%16, %17, %18, %19, %20, %21, %22, %23, %24, %25, %26, %27, %28, %29, %30, %31, "
    "%32, %33, %34, %35, %36, %37, %38, %39, %40, %41, %42, %43, %44, %45, %46, %47, "
    "%48, %49, %50, %51, %52, %53, %54, %55, %56, %57, %58, %59, %60, %61, %62, %63, "
    "%64, %65, %66, %67, %68, %69, %70, %71, %72, %73, %74, %75, %76, %77, %78, %79, "
    "%80, %81, %82, %83, %84, %85, %86, %87, %88, %89, %90, %91, %92, %93, %94, %95, "
    "%96, %97, %98, %99, %100, %101, %102, %103, %104, %105, %106, %107, %108, %109, %110, %111, "
    "%112, %113, %114, %115, %116, %117, %118, %119, %120, %121, %122, %123, %124, %125, %126, %127}, "
    "%128, %129, 1, 1, 1, 0, 1;\n}\n"
    : "+f"(d[0]), "+f"(d[1]), "+f"(d[2]), "+f"(d[3]), "+f"(d[4]), "+f"(d[5]), "+f"(d[6]), "+f"(d[7]),
      "+f"(d[8]), "+f"(d[9]), "+f"(d[10]), "+f"(d[11]), "+f"(d[12]), "+f"(d[13]), "+f"(d[14]), "+f"(d[15]),
      "+f"(d[16]), "+f"(d[17]), "+f"(d[18]), "+f"(d[19]), "+f"(d[20]), "+f"(d[21]), "+f"(d[22]), "+f"(d[23]),
      "+f"(d[24]), "+f"(d[25]), "+f"(d[26]), "+f"(d[27]), "+f"(d[28]), "+f"(d[29]), "+f"(d[30]), "+f"(d[31]),
      "+f"(d[32]), "+f"(d[33]), "+f"(d[34]), "+f"(d[35]), "+f"(d[36]), "+f"(d[37]), "+f"(d[38]), "+f"(d[39]),
      "+f"(d[40]), "+f"(d[41]), "+f"(d[42]), "+f"(d[43]), "+f"(d[44]), "+f"(d[45]), "+f"(d[46]), "+f"(d[47]),
      "+f"(d[48]), "+f"(d[49]), "+f"(d[50]), "+f"(d[51]), "+f"(d[52]), "+f"(d[53]), "+f"(d[54]), "+f"(d[55]),
      "+f"(d[56]), "+f"(d[57]), "+f"(d[58]), "+f"(d[59]), "+f"(d[60]), "+f"(d[61]), "+f"(d[62]), "+f"(d[63]),
      "+f"(d[64]), "+f"(d[65]), "+f"(d[66]), "+f"(d[67]), "+f"(d[68]), "+f"(d[69]), "+f"(d[70]), "+f"(d[71]),
      "+f"(d[72]), "+f"(d[73]), "+f"(d[74]), "+f"(d[75]), "+f"(d[76]), "+f"(d[77]), "+f"(d[78]), "+f"(d[79]),
      "+f"(d[80]), "+f"(d[81]), "+f"(d[82]), "+f"(d[83]), "+f"(d[84]), "+f"(d[85]), "+f"(d[86]), "+f"(d[87]),
      "+f"(d[88]), "+f"(d[89]), "+f"(d[90]), "+f"(d[91]), "+f"(d[92]), "+f"(d[93]), "+f"(d[94]), "+f"(d[95]),
      "+f"(d[96]), "+f"(d[97]), "+f"(d[98]), "+f"(d[99]), "+f"(d[100]), "+f"(d[101]), "+f"(d[102]), "+f"(d[103]),
      "+f"(d[104]), "+f"(d[105]), "+f"(d[106]), "+f"(d[107]), "+f"(d[108]), "+f"(d[109]), "+f"(d[110]), "+f"(d[111]),
      "+f"(d[112]), "+f"(d[113]), "+f"(d[114]), "+f"(d[115]), "+f"(d[116]), "+f"(d[117]), "+f"(d[118]), "+f"(d[119]),
      "+f"(d[120]), "+f"(d[121]), "+f"(d[122]), "+f"(d[123]), "+f"(d[124]), "+f"(d[125]), "+f"(d[126]), "+f"(d[127])
    : "l"(da), "l"(db));
}
__device__ __forceinline__ void wgmma_n128_ss_z(float (&d)[64], uint64_t da, uint64_t db) {
  asm volatile("{\n"
    "wgmma.mma_async.sync.aligned.m64n128k16.f32.bf16.bf16 "
    "{%0, %1, %2, %3, %4, %5, %6, %7, %8, %9, %10, %11, %12, %13, %14, %15, "
    "%16, %17, %18, %19, %20, %21, %22, %23, %24, %25, %26, %27, %28, %29, %30, %31, "
    "%32, %33, %34, %35, %36, %37, %38, %39, %40, %41, %42, %43, %44, %45, %46, %47, "
    "%48, %49, %50, %51, %52, %53, %54, %55, %56, %57, %58, %59, %60, %61, %62, %63}, "
    "%64, %65, 0, 1, 1, 0, 0;\n}\n"
    : "=f"(d[0]), "=f"(d[1]), "=f"(d[2]), "=f"(d[3]), "=f"(d[4]), "=f"(d[5]), "=f"(d[6]), "=f"(d[7]),
      "=f"(d[8]), "=f"(d[9]), "=f"(d[10]), "=f"(d[11]), "=f"(d[12]), "=f"(d[13]), "=f"(d[14]), "=f"(d[15]),
      "=f"(d[16]), "=f"(d[17]), "=f"(d[18]), "=f"(d[19]), "=f"(d[20]), "=f"(d[21]), "=f"(d[22]), "=f"(d[23]),
      "=f"(d[24]), "=f"(d[25]), "=f"(d[26]), "=f"(d[27]), "=f"(d[28]), "=f"(d[29]), "=f"(d[30]), "=f"(d[31]),
      "=f"(d[32]), "=f"(d[33]), "=f"(d[34]), "=f"(d[35]), "=f"(d[36]), "=f"(d[37]), "=f"(d[38]), "=f"(d[39]),
      "=f"(d[40]), "=f"(d[41]), "=f"(d[42]), "=f"(d[43]), "=f"(d[44]), "=f"(d[45]), "=f"(d[46]), "=f"(d[47]),
      "=f"(d[48]), "=f"(d[49]), "=f"(d[50]), "=f"(d[51]), "=f"(d[52]), "=f"(d[53]), "=f"(d[54]), "=f"(d[55]),
      "=f"(d[56]), "=f"(d[57]), "=f"(d[58]), "=f"(d[59]), "=f"(d[60]), "=f"(d[61]), "=f"(d[62]), "=f"(d[63])
    : "l"(da), "l"(db));
}
__device__ __forceinline__ void wgmma_n128_ss(float (&d)[64], uint64_t da, uint64_t db) {
  asm volatile("{\n"
    "wgmma.mma_async.sync.aligned.m64n128k16.f32.bf16.bf16 "
    "{%0, %1, %2, %3, %4, %5, %6, %7, %8, %9, %10, %11, %12, %13, %14, %15, "
    "%16, %17, %18, %19, %20, %21, %22, %23, %24, %25, %26, %27, %28, %29, %30, %31, "
    "%32, %33, %34, %35, %36, %37, %38, %39, %40, %41, %42, %43, %44, %45, %46, %47, "
    "%48, %49, %50, %51, %52, %53, %54, %55, %56, %57, %58, %59, %60, %61, %62, %63}, "
    "%64, %65, 1, 1, 1, 0, 0;\n}\n"
    : "+f"(d[0]), "+f"(d[1]), "+f"(d[2]), "+f"(d[3]), "+f"(d[4]), "+f"(d[5]), "+f"(d[6]), "+f"(d[7]),
      "+f"(d[8]), "+f"(d[9]), "+f"(d[10]), "+f"(d[11]), "+f"(d[12]), "+f"(d[13]), "+f"(d[14]), "+f"(d[15]),
      "+f"(d[16]), "+f"(d[17]), "+f"(d[18]), "+f"(d[19]), "+f"(d[20]), "+f"(d[21]), "+f"(d[22]), "+f"(d[23]),
      "+f"(d[24]), "+f"(d[25]), "+f"(d[26]), "+f"(d[27]), "+f"(d[28]), "+f"(d[29]), "+f"(d[30]), "+f"(d[31]),
      "+f"(d[32]), "+f"(d[33]), "+f"(d[34]), "+f"(d[35]), "+f"(d[36]), "+f"(d[37]), "+f"(d[38]), "+f"(d[39]),
      "+f"(d[40]), "+f"(d[41]), "+f"(d[42]), "+f"(d[43]), "+f"(d[44]), "+f"(d[45]), "+f"(d[46]), "+f"(d[47]),
      "+f"(d[48]), "+f"(d[49]), "+f"(d[50]), "+f"(d[51]), "+f"(d[52]), "+f"(d[53]), "+f"(d[54]), "+f"(d[55]),
      "+f"(d[56]), "+f"(d[57]), "+f"(d[58]), "+f"(d[59]), "+f"(d[60]), "+f"(d[61]), "+f"(d[62]), "+f"(d[63])
    : "l"(da), "l"(db));
}
__device__ __forceinline__ void wgmma_n128_rs_tb_p(float (&d)[64], uint32_t a0, uint32_t a1, uint32_t a2, uint32_t a3, uint64_t db, int sd) {
  asm volatile("{\n.reg .pred p;\nsetp.ne.b32 p, %69, 0;\n"
    "wgmma.mma_async.sync.aligned.m64n128k16.f32.bf16.bf16 "
    "{%0, %1, %2, %3, %4, %5, %6, %7, %8, %9, %10, %11, %12, %13, %14, %15, "
    "%16, %17, %18, %19, %20, %21, %22, %23, %24, %25, %26, %27, %28, %29, %30, %31, "
    "%32, %33, %34, %35, %36, %37, %38, %39, %40, %41, %42, %43, %44, %45, %46, %47, "
    "%48, %49, %50, %51, %52, %53, %54, %55, %56, %57, %58, %59, %60, %61, %62, %63}, "
    "{%64, %65, %66, %67}, %68, p, 1, 1, 1;\n}\n"
    : "+f"(d[0]), "+f"(d[1]), "+f"(d[2]), "+f"(d[3]), "+f"(d[4]), "+f"(d[5]), "+f"(d[6]), "+f"(d[7]),
      "+f"(d[8]), "+f"(d[9]), "+f"(d[10]), "+f"(d[11]), "+f"(d[12]), "+f"(d[13]), "+f"(d[14]), "+f"(d[15]),
      "+f"(d[16]), "+f"(d[17]), "+f"(d[18]), "+f"(d[19]), "+f"(d[20]), "+f"(d[21]), "+f"(d[22]), "+f"(d[23]),
      "+f"(d[24]), "+f"(d[25]), "+f"(d[26]), "+f"(d[27]), "+f"(d[28]), "+f"(d[29]), "+f"(d[30]), "+f"(d[31]),
      "+f"(d[32]), "+f"(d[33]), "+f"(d[34]), "+f"(d[35]), "+f"(d[36]), "+f"(d[37]), "+f"(d[38]), "+f"(d[39]),
      "+f"(d[40]), "+f"(d[41]), "+f"(d[42]), "+f"(d[43]), "+f"(d[44]), "+f"(d[45]), "+f"(d[46]), "+f"(d[47]),
      "+f"(d[48]), "+f"(d[49]), "+f"(d[50]), "+f"(d[51]), "+f"(d[52]), "+f"(d[53]), "+f"(d[54]), "+f"(d[55]),
      "+f"(d[56]), "+f"(d[57]), "+f"(d[58]), "+f"(d[59]), "+f"(d[60]), "+f"(d[61]), "+f"(d[62]), "+f"(d[63])
    : "r"(a0), "r"(a1), "r"(a2), "r"(a3), "l"(db), "r"(sd));
}
__device__ __forceinline__ void wgmma_n128_rs_tb(float (&d)[64], uint32_t a0, uint32_t a1, uint32_t a2, uint32_t a3, uint64_t db) {
  asm volatile("{\n"
    "wgmma.mma_async.sync.aligned.m64n128k16.f32.bf16.bf16 "
    "{%0, %1, %2, %3, %4, %5, %6, %7, %8, %9, %10, %11, %12, %13, %14, %15, "
    "%16, %17, %18, %19, %20, %21, %22, %23, %24, %25, %26, %27, %28, %29, %30, %31, "
    "%32, %33, %34, %35, %36, %37, %38, %39, %40, %41, %42, %43, %44, %45, %46, %47, "
    "%48, %49, %50, %51, %52, %53, %54, %55, %56, %57, %58, %59, %60, %61, %62, %63}, "
    "{%64, %65, %66, %67}, %68, 1, 1, 1, 1;\n}\n"
    : "+f"(d[0]), "+f"(d[1]), "+f"(d[2]), "+f"(d[3]), "+f"(d[4]), "+f"(d[5]), "+f"(d[6]), "+f"(d[7]),
      "+f"(d[8]), "+f"(d[9]), "+f"(d[10]), "+f"(d[11]), "+f"(d[12]), "+f"(d[13]), "+f"(d[14]), "+f"(d[15]),
      "+f"(d[16]), "+f"(d[17]), "+f"(d[18]), "+f"(d[19]), "+f"(d[20]), "+f"(d[21]), "+f"(d[22]), "+f"(d[23]),
      "+f"(d[24]), "+f"(d[25]), "+f"(d[26]), "+f"(d[27]), "+f"(d[28]), "+f"(d[29]), "+f"(d[30]), "+f"(d[31]),
      "+f"(d[32]), "+f"(d[33]), "+f"(d[34]), "+f"(d[35]), "+f"(d[36]), "+f"(d[37]), "+f"(d[38]), "+f"(d[39]),
      "+f"(d[40]), "+f"(d[41]), "+f"(d[42]), "+f"(d[43]), "+f"(d[44]), "+f"(d[45]), "+f"(d[46]), "+f"(d[47]),
      "+f"(d[48]), "+f"(d[49]), "+f"(d[50]), "+f"(d[51]), "+f"(d[52]), "+f"(d[53]), "+f"(d[54]), "+f"(d[55]),
      "+f"(d[56]), "+f"(d[57]), "+f"(d[58]), "+f"(d[59]), "+f"(d[60]), "+f"(d[61]), "+f"(d[62]), "+f"(d[63])
    : "r"(a0), "r"(a1), "r"(a2), "r"(a3), "l"(db));
}
__device__ __forceinline__ void wgmma_n32_ss_tatb_z(float (&d)[16], uint64_t da, uint64_t db) {
  asm volatile("{\n"
    "wgmma.mma_async.sync.aligned.m64n32k16.f32.bf16.bf16 "
    "{%0, %1, %2, %3, %4, %5, %6, %7, %8, %9, %10, %11, %12, %13, %14, %15}, "
    "%16, %17, 0, 1, 1, 1, 1;\n}\n"
    : "=f"(d[0]), "=f"(d[1]), "=f"(d[2]), "=f"(d[3]), "=f"(d[4]), "=f"(d[5]), "=f"(d[6]), "=f"(d[7]),
      "=f"(d[8]), "=f"(d[9]), "=f"(d[10]), "=f"(d[11]), "=f"(d[12]), "=f"(d[13]), "=f"(d[14]), "=f"(d[15])
    : "l"(da), "l"(db));
}
__device__ __forceinline__ void wgmma_n32_ss_tatb(float (&d)[16], uint64_t da, uint64_t db) {
  asm volatile("{\n"
    "wgmma.mma_async.sync.aligned.m64n32k16.f32.bf16.bf16 "
    "{%0, %1, %2, %3, %4, %5, %6, %7, %8, %9, %10, %11, %12, %13, %14, %15}, "
    "%16, %17, 1, 1, 1, 1, 1;\n}\n"
    : "+f"(d[0]), "+f"(d[1]), "+f"(d[2]), "+f"(d[3]), "+f"(d[4]), "+f"(d[5]), "+f"(d[6]), "+f"(d[7]),
      "+f"(d[8]), "+f"(d[9]), "+f"(d[10]), "+f"(d[11]), "+f"(d[12]), "+f"(d[13]), "+f"(d[14]), "+f"(d[15])
    : "l"(da), "l"(db));
}
__device__ __forceinline__ void wgmma_n8_ss_ta_z(float (&d)[4], uint64_t da, uint64_t db) {
  asm volatile("{\n"
    "wgmma.mma_async.sync.aligned.m64n8k16.f32.bf16.bf16 "
    "{%0, %1, %2, %3}, "
    "%4, %5, 0, 1, 1, 1, 0;\n}\n"
    : "=f"(d[0]), "=f"(d[1]), "=f"(d[2]), "=f"(d[3])
    : "l"(da), "l"(db));
}
__device__ __forceinline__ void wgmma_n8_ss_ta(float (&d)[4], uint64_t da, uint64_t db) {
  asm volatile("{\n"
    "wgmma.mma_async.sync.aligned.m64n8k16.f32.bf16.bf16 "
    "{%0, %1, %2, %3}, "
    "%4, %5, 1, 1, 1, 1, 0;\n}\n"
    : "+f"(d[0]), "+f"(d[1]), "+f"(d[2]), "+f"(d[3])
    : "l"(da), "l"(db));
}

constexpr int G_STAGES = 4;
constexpr int G_A_BYTES = 128 * 64 * 2;
constexpr int G_B_BYTES = 256 * 64 * 2;
constexpr int G_STAGE_BYTES = G_A_BYTES + G_B_BYTES;
constexpr int G_STG_OFF = G_STAGES * G_STAGE_BYTES;
constexpr int G_ONES_OFF = G_STG_OFF + 32768;
constexpr int G_BAR_OFF = G_ONES_OFF + 256;
constexpr int G_SMEM = G_BAR_OFF + 128 + 1024;

template <bool FIRST>
__device__ __forceinline__ void gemm_step(float (&acc)[128], uint32_t sa, int wg) {
  const uint64_t da = make_desc(sa + wg * 8192, 16, 1024);
  const uint64_t db = make_desc(sa + G_A_BYTES, 8192, 1024);
  wg_fence();
  if (FIRST)
    wgmma_n256_ss_tb_z(acc, da, db);
  else
    wgmma_n256_ss_tb(acc, da, db);
#pragma unroll
  for (int kk = 1; kk < 4; kk++) wgmma_n256_ss_tb(acc, da + kk * 2, db + kk * 128);
  wg_commit();
}

enum { T_KV = 0, T_QA = 1, T_QB = 2, T_KB = 3, T_VB = 4 };
constexpr int K1_MAXT = 10;
struct K1Params {
  CUtensorMap x, ckv, wqkv, wq, wuk, wuv, qkv_st, a3_st;
  const __nv_bfloat16* wphi;
  const __nv_bfloat16* xin;
  const __nv_bfloat16* gatew;
  uint16_t tiles[66][K1_MAXT];
};

__device__ __forceinline__ void pack_acc(const float (&acc)[128], uint32_t (&pk)[64]) {
#pragma unroll
  for (int i = 0; i < 64; i++) pk[i] = pack_bf16(acc[2 * i], acc[2 * i + 1]);
}
template <int J0>
__device__ __forceinline__ void stage_box(const uint32_t (&pk)[64], uint32_t box, int lane) {
  const uint32_t row = (lane & 7) + ((lane >> 3) & 1) * 8;
  const uint32_t base = box + row * 128;
#pragma unroll
  for (int i = 0; i < 4; i++) {
    const int j = J0 + 2 * i;
    const uint32_t ch = (uint32_t)(2 * i + (lane >> 4)) ^ (lane & 7);
    stsm4(base + ch * 16, pk[2 * j], pk[2 * j + 1], pk[2 * j + 2], pk[2 * j + 3]);
  }
}

template <int J0>
__device__ __forceinline__ void hedgehog(const uint32_t (&acc)[64], const __nv_bfloat16* wphi_h, int lane,
                                         uint32_t (&phi)[16]) {
  const int g = lane >> 2, t = lane & 3;
  float p[4][4];
#pragma unroll
  for (int j = 0; j < 4; j++)
#pragma unroll
    for (int c = 0; c < 4; c++) p[j][c] = 0.f;
#pragma unroll
  for (int ks = 0; ks < 2; ks++) {
    const int j = J0 + 2 * ks;
    const uint32_t a0 = acc[2 * j], a1 = acc[2 * j + 1], a2 = acc[2 * j + 2], a3 = acc[2 * j + 3];
    const __nv_bfloat16* w = wphi_h + (ks * 16 + 2 * t) * 32 + 4 * g;
    const uint2 w0 = __ldg((const uint2*)(w)), w1 = __ldg((const uint2*)(w + 32));
    const uint2 w2 = __ldg((const uint2*)(w + 8 * 32)), w3 = __ldg((const uint2*)(w + 9 * 32));
    mma16816(p[0], a0, a1, a2, a3, __byte_perm(w0.x, w1.x, 0x5410), __byte_perm(w2.x, w3.x, 0x5410));
    mma16816(p[1], a0, a1, a2, a3, __byte_perm(w0.x, w1.x, 0x7632), __byte_perm(w2.x, w3.x, 0x7632));
    mma16816(p[2], a0, a1, a2, a3, __byte_perm(w0.y, w1.y, 0x5410), __byte_perm(w2.y, w3.y, 0x5410));
    mma16816(p[3], a0, a1, a2, a3, __byte_perm(w0.y, w1.y, 0x7632), __byte_perm(w2.y, w3.y, 0x7632));
  }
  const float L2E = 1.4426950408889634f;
#pragma unroll
  for (int r = 0; r < 2; r++) {
    float mx = fmaxf(p[0][2 * r], p[0][2 * r + 1]), mn = fminf(p[0][2 * r], p[0][2 * r + 1]);
#pragma unroll
    for (int j = 1; j < 4; j++) {
      mx = fmaxf(mx, fmaxf(p[j][2 * r], p[j][2 * r + 1]));
      mn = fminf(mn, fminf(p[j][2 * r], p[j][2 * r + 1]));
    }
    mx = fmaxf(mx, __shfl_xor_sync(0xffffffffu, mx, 1));
    mn = fminf(mn, __shfl_xor_sync(0xffffffffu, mn, 1));
    mx = fmaxf(mx, __shfl_xor_sync(0xffffffffu, mx, 2));
    mn = fminf(mn, __shfl_xor_sync(0xffffffffu, mn, 2));
    const float mxs = mx * L2E, mns = mn * L2E;
    float ep[8], en[8], sp = 0.f, sn = 0.f;
#pragma unroll
    for (int j = 0; j < 4; j++)
#pragma unroll
      for (int c = 0; c < 2; c++) {
        const float v = p[j][2 * r + c];
        ep[2 * j + c] = ex2(fmaf(v, L2E, -mxs));
        en[2 * j + c] = ex2(fmaf(v, -L2E, mns));
        sp += ep[2 * j + c];
        sn += en[2 * j + c];
      }
    sp += __shfl_xor_sync(0xffffffffu, sp, 1);
    sn += __shfl_xor_sync(0xffffffffu, sn, 1);
    sp += __shfl_xor_sync(0xffffffffu, sp, 2);
    sn += __shfl_xor_sync(0xffffffffu, sn, 2);
    const float ip = rcp(sp), in = rcp(sn);
#pragma unroll
    for (int j = 0; j < 4; j++) {
      phi[2 * j + r] = pack_bf16(ep[2 * j] * ip, ep[2 * j + 1] * ip);
      phi[8 + 2 * j + r] = pack_bf16(en[2 * j] * in, en[2 * j + 1] * in);
    }
  }
}

template <int J0>
__device__ __forceinline__ void epi_kv_half(const uint32_t (&acc)[64], const K1Params& P, int head0, int part, uint32_t stg,
                                            uint32_t ones, int wg, int tid) {
  const int lane = tid & 31, warp = tid >> 5;
  const uint32_t phibox = stg + warp * 2048, vbox = stg + 8192 + warp * 2048;
  const uint32_t row = (lane & 7) + ((lane >> 3) & 1) * 8;
  if (lane == 0) bulk_wait_read<0>();
  __syncwarp();
#pragma unroll
  for (int hh = 0; hh < 2; hh++) {
    uint32_t phi[16];
    if (hh == 0)
      hedgehog<J0>(acc, P.wphi + (size_t)head0 * 1024, lane, phi);
    else
      hedgehog<J0 + 4>(acc, P.wphi + (size_t)(head0 + 1) * 1024, lane, phi);
    bar_sync(1 + wg, 128);
    if (hh == 0) stage_box<J0 + 8>(acc, vbox, lane);
#pragma unroll
    for (int i = 0; i < 4; i++) {
      const uint32_t ch = (uint32_t)(2 * i + (lane >> 4)) ^ (lane & 7);
      stsm4(phibox + row * 128 + ch * 16, phi[4 * i], phi[4 * i + 1], phi[4 * i + 2], phi[4 * i + 3]);
    }
    fence_async_smem();
    bar_sync(1 + wg, 128);
    float d[16], z[4];
    const uint64_t da = make_desc(stg, 8192, 1024);
    const uint64_t db = make_desc(stg + 8192 + hh * 64, 8192, 1024);
    const uint64_t dones = (uint64_t)((ones & 0x3FFFF) >> 4) | ((uint64_t)(128 >> 4) << 16) | ((uint64_t)(128 >> 4) << 32);
    wg_fence();
    wgmma_n32_ss_tatb_z(d, da, db);
    wgmma_n8_ss_ta_z(z, da, dones);
#pragma unroll
    for (int kk = 1; kk < 4; kk++) {
      wgmma_n32_ss_tatb(d, da + kk * 128, db + kk * 128);
      wgmma_n8_ss_ta(z, da + kk * 128, dones);
    }
    wg_commit();
    wg_wait<0>();
    reg_fence(d);
    reg_fence(z);
    float* dst = g_part + ((size_t)(head0 + hh) * 32 + part) * 2112;
#pragma unroll
    for (int i = 0; i < 4; i++)
      *(float4*)(dst + (i * 128 + tid) * 4) = make_float4(d[4 * i], d[4 * i + 1], d[4 * i + 2], d[4 * i + 3]);
    if ((lane & 3) == 0) {
      dst[2048 + warp * 16 + (lane >> 2)] = z[0];
      dst[2048 + warp * 16 + 8 + (lane >> 2)] = z[2];
    }
  }
}

template <int J0>
__device__ __forceinline__ void epi_qa_box(const uint32_t (&acc)[64], const K1Params& P, int head0, float g0, float g1,
                                           uint32_t box, int lane) {
  const uint32_t row = (lane & 7) + ((lane >> 3) & 1) * 8;
  uint32_t o[2][8];
#pragma unroll
  for (int hh = 0; hh < 2; hh++) {
    uint32_t phi[16];
    if (hh == 0)
      hedgehog<J0>(acc, P.wphi + (size_t)head0 * 1024, lane, phi);
    else
      hedgehog<J0 + 4>(acc, P.wphi + (size_t)(head0 + 1) * 1024, lane, phi);
    float nm[5][4];
#pragma unroll
    for (int j = 0; j < 5; j++)
#pragma unroll
      for (int c = 0; c < 4; c++) nm[j][c] = 0.f;
    const uint4* kf = (const uint4*)g_kvfrag + (size_t)(head0 + hh) * 320 + lane;
    uint32_t b[40];
#pragma unroll
    for (int i = 0; i < 10; i++) {
      const uint4 v = __ldcg(kf + i * 32);
      b[4 * i] = v.x; b[4 * i + 1] = v.y; b[4 * i + 2] = v.z; b[4 * i + 3] = v.w;
    }
#pragma unroll
    for (int ks = 0; ks < 4; ks++)
#pragma unroll
      for (int j = 0; j < 5; j++)
        mma16816(nm[j], phi[4 * ks], phi[4 * ks + 1], phi[4 * ks + 2], phi[4 * ks + 3], b[ks * 10 + 2 * j],
                 b[ks * 10 + 2 * j + 1]);
    const float s0 = g0 * rcp(nm[4][0] + 1e-6f), s1 = g1 * rcp(nm[4][2] + 1e-6f);
#pragma unroll
    for (int j = 0; j < 4; j++) {
      o[hh][2 * j] = pack_bf16(nm[j][0] * s0, nm[j][1] * s0);
      o[hh][2 * j + 1] = pack_bf16(nm[j][2] * s1, nm[j][3] * s1);
    }
  }
  if (lane == 0) bulk_wait_read<1>();
  __syncwarp();
#pragma unroll
  for (int i = 0; i < 4; i++) {
    const uint32_t ch = (uint32_t)(2 * i + (lane >> 4)) ^ (lane & 7);
    stsm4(box + row * 128 + ch * 16, o[i >> 1][(i & 1) * 4], o[i >> 1][(i & 1) * 4 + 1], o[i >> 1][(i & 1) * 4 + 2],
          o[i >> 1][(i & 1) * 4 + 3]);
  }
}

template <int Q>
__device__ __forceinline__ void epi_plain_box(const uint32_t (&acc)[64], const CUtensorMap* m, uint32_t stg, int warp, int lane,
                                              int x, int y) {
  const uint32_t box = stg + (Q & 1) * 8192 + warp * 2048;
  if (lane == 0) bulk_wait_read<1>();
  __syncwarp();
  stage_box<Q * 8>(acc, box, lane);
  fence_async_smem();
  __syncwarp();
  if (lane == 0) {
    tma_store(m, box, x, y);
    bulk_commit();
  }
}
template <int Q>
__device__ __forceinline__ void epi_qa(const uint32_t (&acc)[64], const K1Params& P, uint32_t stg, int warp, int lane, int col,
                                       int y, float g0, float g1) {
  const uint32_t box = stg + (Q & 1) * 8192 + warp * 2048;
  epi_qa_box<Q * 8>(acc, P, col * 8 + Q * 2, g0, g1, box, lane);
  fence_async_smem();
  __syncwarp();
  if (lane == 0) {
    tma_store(&P.a3_st, box, col * 256 + Q * 64, y);
    bulk_commit();
  }
}

__global__ void __cluster_dims__(2, 1, 1) __launch_bounds__(384, 1) k1_proj(const __grid_constant__ K1Params P) {
  extern __shared__ uint8_t smem_raw[];
  const uint32_t sb = (smem_u32(smem_raw) + 1023) & ~1023u;
  const uint32_t full0 = sb + G_BAR_OFF, empty0 = full0 + 8 * G_STAGES;
  const int tid = threadIdx.x, wgid = tid >> 7;
  const uint32_t rank = cluster_rank();
  const int cl = blockIdx.x >> 1;
  if (tid == 0) {
    for (int s = 0; s < G_STAGES; s++) {
      mbar_init(full0 + 8 * s, 1);
      mbar_init(empty0 + 8 * s, 4);
    }
    asm volatile("fence.mbarrier_init.release.cluster;" ::: "memory");
  }
  if (tid >= 128 && tid < 192) {
    asm volatile("st.shared.u32 [%0], %1;" ::"r"(sb + G_ONES_OFF + (tid - 128) * 4), "r"(0x3F803F80u) : "memory");
    fence_async_smem();
  }
  pdl_launch();
  cluster_arrive();
  cluster_wait();

  if (wgid == 0) {
    reg_dec<56>();
    const int warp = tid >> 5, lane = tid & 31;
    if (warp == 0) {
      if (lane == 0) {
        int stage = 0;
        uint32_t phase = 1;
        for (int it = 0; it < K1_MAXT; it++) {
          const uint32_t code = P.tiles[cl][it];
          if (code == 0xFFFF) break;
          const int type = code >> 8, rp = (code >> 5) & 7, col = code & 31;
          const CUtensorMap* ma = (type <= T_QB) ? &P.x : &P.ckv;
          const CUtensorMap* mb = (type <= T_QA) ? &P.wqkv : (type == T_QB) ? &P.wq : (type == T_KB) ? &P.wuk : &P.wuv;
          const int nk = (type <= T_QB) ? 16 : 8;
          int c0, c1;
          if (type == T_KV) {
            c0 = 1024 + col * 128 + rank * 64;
            c1 = c0 + 1024;
          } else {
            c0 = col * 256 + rank * 128;
            c1 = c0 + 64;
          }
          const int row0 = rp * 256 + rank * 128;
          for (int k = 0; k < nk; k++) {
            mbar_wait_cluster(empty0 + 8 * stage, phase);
            const uint32_t sa = sb + stage * G_STAGE_BYTES, sbb = sa + G_A_BYTES + rank * 16384;
            const uint32_t fb = full0 + 8 * stage;
            mbar_expect_tx(fb, G_STAGE_BYTES);
            tma_load(sa, ma, k * 64, row0, fb);
            tma_load_mc(sbb, mb, c0, k * 64, fb, 3);
            tma_load_mc(sbb + 8192, mb, c1, k * 64, fb, 3);
            if (++stage == G_STAGES) { stage = 0; phase ^= 1; }
          }
        }
        for (int s = 0; s < G_STAGES; s++) {
          mbar_wait_cluster(empty0 + 8 * stage, phase);
          if (++stage == G_STAGES) { stage = 0; phase ^= 1; }
        }
      }
    } else if (blockIdx.x < 128) {
      const int b = blockIdx.x;
      for (int r = warp - 1; r < 16; r += 3) {
        const int row = b * 16 + r;
        float acc = 0.f;
#pragma unroll
        for (int i = 0; i < 4; i++) {
          const uint4 xv = __ldg((const uint4*)(P.xin + (size_t)row * 1024) + i * 32 + lane);
          const uint4 gv = __ldg((const uint4*)P.gatew + i * 32 + lane);
          const uint32_t xs[4] = {xv.x, xv.y, xv.z, xv.w}, gs[4] = {gv.x, gv.y, gv.z, gv.w};
#pragma unroll
          for (int c = 0; c < 4; c++) {
            acc = fmaf(__uint_as_float(xs[c] << 16), __uint_as_float(gs[c] << 16), acc);
            acc = fmaf(__uint_as_float(xs[c] & 0xffff0000u), __uint_as_float(gs[c] & 0xffff0000u), acc);
          }
        }
#pragma unroll
        for (int o = 16; o > 0; o >>= 1) acc += __shfl_xor_sync(0xffffffffu, acc, o);
        if (lane == 0) g_gate[row] = rcp(1.f + ex2(-acc * 1.4426950408889634f));
      }
      const int h = b >> 2, q = b & 3;
      if (lane == 0) spin_until(&g_cnt[h >> 2], 32);
      __syncwarp();
      const float* src = g_part + (size_t)h * 32 * 2112;
      __nv_bfloat16* dst = (__nv_bfloat16*)(g_kvfrag + h * 1280);
      if (warp < 3) {
#pragma unroll 1
        for (int ii = 0; ii < 2; ii++) {
          const int i = (warp - 1) * 2 + ii;
          float4 s = make_float4(0.f, 0.f, 0.f, 0.f);
#pragma unroll 8
          for (int p = 0; p < 32; p++) {
            const float4 v = __ldcg((const float4*)(src + p * 2112) + i * 128 + q * 32 + lane);
            s.x += v.x; s.y += v.y; s.z += v.z; s.w += v.w;
          }
          const int g = lane >> 2, t = lane & 3;
          const float vals[4] = {s.x, s.y, s.z, s.w};
#pragma unroll
          for (int e = 0; e < 4; e++) {
            const int r = e >> 1, c = e & 1;
            const int reg = q * 10 + 2 * i + r, l2 = (2 * t + c) * 4 + (g >> 1);
            dst[(((reg >> 2) * 32 + l2) * 4 + (reg & 3)) * 2 + (g & 1)] = __float2bfloat16(vals[e]);
          }
        }
      } else {
        const int f = lane & 15;
        float s = 0.f;
#pragma unroll 8
        for (int p = lane >> 4; p < 32; p += 2) s += __ldcg(src + p * 2112 + 2048 + q * 16 + f);
        s += __shfl_xor_sync(0xffffffffu, s, 16);
        const __nv_bfloat16 zb = __float2bfloat16(s);
        const int reg = q * 10 + 8 + (f >> 3);
#pragma unroll
        for (int n = 0; n < 4; n++) {
          const int l2 = ((lane >> 4) * 4 + n) * 4 + ((f & 7) >> 1);
          dst[(((reg >> 2) * 32 + l2) * 4 + (reg & 3)) * 2 + (f & 1)] = zb;
        }
      }
      __threadfence();
      __syncwarp();
      if (lane == 0) red_release(&g_cnt[8], 1);
    }
  } else {
    reg_inc<224>();
    const int wg = wgid - 1, t128 = tid & 127, warp = t128 >> 5, lane = tid & 31;
    const uint32_t stg = sb + G_STG_OFF + wg * 16384;
    int stage = 0;
    uint32_t phase = 0;
    float acc[128];
    for (int it = 0; it < K1_MAXT; it++) {
      const uint32_t code = P.tiles[cl][it];
      if (code == 0xFFFF) break;
      const int type = code >> 8, rp = (code >> 5) & 7, col = code & 31;
      const int nk = (type <= T_QB) ? 16 : 8;
      mbar_wait(full0 + 8 * stage, phase);
      gemm_step<true>(acc, sb + stage * G_STAGE_BYTES, wg);
      int prev = stage;
      if (++stage == G_STAGES) { stage = 0; phase ^= 1; }
      for (int k = 1; k < nk; k++) {
        mbar_wait(full0 + 8 * stage, phase);
        gemm_step<false>(acc, sb + stage * G_STAGE_BYTES, wg);
        wg_wait<1>();
        if (t128 < 2) mbar_arrive_cluster(empty0 + 8 * prev, t128);
        prev = stage;
        if (++stage == G_STAGES) { stage = 0; phase ^= 1; }
      }
      wg_wait<0>();
      reg_fence(acc);
      if (t128 < 2) mbar_arrive_cluster(empty0 + 8 * prev, t128);
      const int row0 = rp * 256 + rank * 128 + wg * 64 + warp * 16;
      uint32_t pk[64];
      pack_acc(acc, pk);
      if (type >= T_QB) {
        const int y = ((type - T_QB) * 32 + col * 2) * SEQ + row0;
        epi_plain_box<0>(pk, &P.qkv_st, stg, warp, lane, 0, y);
        epi_plain_box<1>(pk, &P.qkv_st, stg, warp, lane, 64, y);
        epi_plain_box<2>(pk, &P.qkv_st, stg, warp, lane, 0, y + SEQ);
        epi_plain_box<3>(pk, &P.qkv_st, stg, warp, lane, 64, y + SEQ);
      } else if (type == T_KV) {
        const int part = rp * 4 + rank * 2 + wg;
        epi_kv_half<0>(pk, P, col * 4, part, stg, sb + G_ONES_OFF, wg, t128);
        epi_kv_half<16>(pk, P, col * 4 + 2, part, stg, sb + G_ONES_OFF, wg, t128);
        __threadfence();
        bar_sync(1 + wg, 128);
        if (t128 == 0) red_release(&g_cnt[col], 1);
      } else {
        if (lane == 0) spin_until(&g_cnt[8], 128 * 3);
        __syncwarp();
        const float g0 = __ldcg(g_gate + row0 + (lane >> 2)), g1 = __ldcg(g_gate + row0 + 8 + (lane >> 2));
        epi_qa<0>(pk, P, stg, warp, lane, col, row0, g0, g1);
        epi_qa<1>(pk, P, stg, warp, lane, col, row0, g0, g1);
        epi_qa<2>(pk, P, stg, warp, lane, col, row0, g0, g1);
        epi_qa<3>(pk, P, stg, warp, lane, col, row0, g0, g1);
      }
    }
    if (lane == 0) bulk_wait<0>();
  }
}

constexpr int A_SLOTS = 5;
constexpr int A_TILE = 32768;
constexpr int A_Q_OFF = 0;
constexpr int A_RING_OFF = 2 * A_TILE;
constexpr int A_BAR_OFF = A_RING_OFF + A_SLOTS * A_TILE;
constexpr int A_SMEM = A_BAR_OFF + 256 + 1024;
constexpr int K2_MAXI = 8;
struct K2Params {
  CUtensorMap qkv_ld, a3_st;
  uint16_t items[132][K2_MAXI];
};

__device__ __forceinline__ void attn_qk(float (&S)[64], uint32_t qaddr, uint32_t kaddr) {
  const uint64_t da = make_desc(qaddr, 16, 1024), db = make_desc(kaddr, 16, 1024);
  wgmma_n128_ss_z(S, da, db);
#pragma unroll
  for (int kk = 1; kk < 8; kk++) {
    const int off = (kk >> 2) * 1024 + (kk & 3) * 2;
    wgmma_n128_ss(S, da + off, db + off);
  }
}
__device__ __forceinline__ void attn_pv(float (&O)[64], const uint32_t (&Pr)[32], uint32_t vaddr, int accum) {
  const uint64_t db = make_desc(vaddr, 16384, 1024);
  wgmma_n128_rs_tb_p(O, Pr[0], Pr[1], Pr[2], Pr[3], db, accum);
#pragma unroll
  for (int kk = 1; kk < 8; kk++)
    wgmma_n128_rs_tb(O, Pr[4 * kk], Pr[4 * kk + 1], Pr[4 * kk + 2], Pr[4 * kk + 3], db + kk * 128);
}
constexpr float A_SCALE = 0.08838834764831845f * 1.4426950408889634f;

__device__ __forceinline__ void attn_mask(float (&S)[64], int r0, int t) {
#pragma unroll
  for (int j = 0; j < 16; j++) {
    const int c = 8 * j + 2 * t;
    if (c > r0) S[4 * j] = -INFINITY;
    if (c + 1 > r0) S[4 * j + 1] = -INFINITY;
    if (c > r0 + 8) S[4 * j + 2] = -INFINITY;
    if (c + 1 > r0 + 8) S[4 * j + 3] = -INFINITY;
  }
}
template <bool FIRST>
__device__ __forceinline__ void attn_softmax(float (&S)[64], float& m0, float& m1, float& l0, float& l1, float& a0,
                                             float& a1) {
  float x0 = fmaxf(S[0], S[1]), x1 = fmaxf(S[2], S[3]), y0 = fmaxf(S[4], S[5]), y1 = fmaxf(S[6], S[7]);
#pragma unroll
  for (int j = 2; j < 16; j += 2) {
    x0 = fmaxf(x0, fmaxf(S[4 * j], S[4 * j + 1]));
    x1 = fmaxf(x1, fmaxf(S[4 * j + 2], S[4 * j + 3]));
    y0 = fmaxf(y0, fmaxf(S[4 * j + 4], S[4 * j + 5]));
    y1 = fmaxf(y1, fmaxf(S[4 * j + 6], S[4 * j + 7]));
  }
  x0 = fmaxf(x0, y0);
  x1 = fmaxf(x1, y1);
  x0 = fmaxf(x0, __shfl_xor_sync(0xffffffffu, x0, 1));
  x1 = fmaxf(x1, __shfl_xor_sync(0xffffffffu, x1, 1));
  x0 = fmaxf(x0, __shfl_xor_sync(0xffffffffu, x0, 2));
  x1 = fmaxf(x1, __shfl_xor_sync(0xffffffffu, x1, 2));
  if (!FIRST) {
    x0 = fmaxf(x0, m0);
    x1 = fmaxf(x1, m1);
    a0 = ex2((m0 - x0) * A_SCALE);
    a1 = ex2((m1 - x1) * A_SCALE);
  }
  m0 = x0;
  m1 = x1;
  const float c0 = x0 * A_SCALE, c1 = x1 * A_SCALE;
  float s0 = 0.f, s1 = 0.f, u0 = 0.f, u1 = 0.f;
#pragma unroll
  for (int j = 0; j < 16; j++) {
    S[4 * j] = ex2(fmaf(S[4 * j], A_SCALE, -c0));
    S[4 * j + 1] = ex2(fmaf(S[4 * j + 1], A_SCALE, -c0));
    S[4 * j + 2] = ex2(fmaf(S[4 * j + 2], A_SCALE, -c1));
    S[4 * j + 3] = ex2(fmaf(S[4 * j + 3], A_SCALE, -c1));
    s0 += S[4 * j];
    u0 += S[4 * j + 1];
    s1 += S[4 * j + 2];
    u1 += S[4 * j + 3];
  }
  if (FIRST) {
    l0 = s0 + u0;
    l1 = s1 + u1;
  } else {
    l0 = fmaf(l0, a0, s0 + u0);
    l1 = fmaf(l1, a1, s1 + u1);
  }
}
__device__ __forceinline__ void attn_pack(const float (&S)[64], uint32_t (&Pr)[32]) {
#pragma unroll
  for (int i = 0; i < 32; i++) Pr[i] = pack_bf16(S[2 * i], S[2 * i + 1]);
}
__device__ __forceinline__ void attn_epilogue(const float (&O)[64], float l0, float l1, float g0, float g1,
                                              const CUtensorMap* m, uint32_t qrows, int lane, int x, int y) {
  l0 += __shfl_xor_sync(0xffffffffu, l0, 1);
  l1 += __shfl_xor_sync(0xffffffffu, l1, 1);
  l0 += __shfl_xor_sync(0xffffffffu, l0, 2);
  l1 += __shfl_xor_sync(0xffffffffu, l1, 2);
  const float i0 = (1.f - g0) * rcp(l0), i1 = (1.f - g1) * rcp(l1);
  const uint32_t row = (lane & 7) + ((lane >> 3) & 1) * 8;
#pragma unroll
  for (int i = 0; i < 8; i++) {
    const int j = 2 * i;
    const uint32_t ch = (uint32_t)(2 * (i & 3) + (lane >> 4)) ^ (lane & 7);
    stsm4(qrows + (i >> 2) * 16384 + row * 128 + ch * 16, pack_bf16(O[4 * j] * i0, O[4 * j + 1] * i0),
          pack_bf16(O[4 * j + 2] * i1, O[4 * j + 3] * i1), pack_bf16(O[4 * j + 4] * i0, O[4 * j + 5] * i0),
          pack_bf16(O[4 * j + 6] * i1, O[4 * j + 7] * i1));
  }
  fence_async_smem();
  __syncwarp();
  if (lane == 0) {
    tma_store(m, qrows, x, y);
    tma_store(m, qrows + 16384, x + 64, y);
    bulk_commit();
  }
}

__global__ void __launch_bounds__(384, 1) k2_attn(const __grid_constant__ K2Params P) {
  extern __shared__ uint8_t smem_raw[];
  const uint32_t sb = (smem_u32(smem_raw) + 1023) & ~1023u;
  const uint32_t full0 = sb + A_BAR_OFF, empty0 = full0 + 8 * A_SLOTS, qfull0 = empty0 + 8 * A_SLOTS, qempty0 = qfull0 + 16;
  const int tid = threadIdx.x, wgid = tid >> 7;
  const uint16_t* items = P.items[blockIdx.x];
  if (tid == 0) {
    for (int s = 0; s < A_SLOTS; s++) {
      mbar_init(full0 + 8 * s, 1);
      mbar_init(empty0 + 8 * s, 2);
    }
    for (int s = 0; s < 2; s++) {
      mbar_init(qfull0 + 8 * s, 1);
      mbar_init(qempty0 + 8 * s, 8);
    }
    asm volatile("fence.mbarrier_init.release.cluster;" ::: "memory");
    tma_prefetch_desc(&P.qkv_ld);
    tma_prefetch_desc(&P.a3_st);
  }
  pdl_launch();
  __syncthreads();
  pdl_wait();

  if (wgid == 0) {
    reg_dec<40>();
    const int warp = tid >> 5, lane = tid & 31;
    if (warp == 0 && lane == 0) {
      int slot = 0;
      uint32_t phase = 1;
      int vrow = -1;
      for (int it = 0; it < K2_MAXI; it++) {
        const uint32_t code = items[it];
        if (code == 0xFFFF) break;
        const int h = code >> 4, qt = code & 15;
        for (int j = qt; j >= 0; j--) {
          {
            mbar_wait(empty0 + 8 * slot, phase);
            const uint32_t dst = sb + A_RING_OFF + slot * A_TILE, fb = full0 + 8 * slot;
            const int krow = (32 + h) * SEQ + j * 128;
            mbar_expect_tx(fb, A_TILE);
            tma_load(dst, &P.qkv_ld, 0, krow, fb);
            tma_load(dst + 16384, &P.qkv_ld, 64, krow, fb);
            if (++slot == A_SLOTS) { slot = 0; phase ^= 1; }
          }
          if (vrow >= 0) {
            mbar_wait(empty0 + 8 * slot, phase);
            const uint32_t dst = sb + A_RING_OFF + slot * A_TILE, fb = full0 + 8 * slot;
            mbar_expect_tx(fb, A_TILE);
            tma_load(dst, &P.qkv_ld, 0, vrow, fb);
            tma_load(dst + 16384, &P.qkv_ld, 64, vrow, fb);
            if (++slot == A_SLOTS) { slot = 0; phase ^= 1; }
          }
          vrow = (64 + h) * SEQ + j * 128;
        }
      }
      if (vrow >= 0) {
        mbar_wait(empty0 + 8 * slot, phase);
        const uint32_t dst = sb + A_RING_OFF + slot * A_TILE, fb = full0 + 8 * slot;
        mbar_expect_tx(fb, A_TILE);
        tma_load(dst, &P.qkv_ld, 0, vrow, fb);
        tma_load(dst + 16384, &P.qkv_ld, 64, vrow, fb);
      }
    } else if (warp == 1 && lane == 0) {
      for (int it = 0; it < K2_MAXI; it++) {
        const uint32_t code = items[it];
        if (code == 0xFFFF) break;
        const int h = code >> 4, qt = code & 15;
        const int b = it & 1;
        mbar_wait(qempty0 + 8 * b, ((it >> 1) & 1) ^ 1);
        const uint32_t dst = sb + A_Q_OFF + b * A_TILE, fb = qfull0 + 8 * b;
        mbar_expect_tx(fb, A_TILE);
        tma_load(dst, &P.qkv_ld, 0, h * SEQ + qt * 128, fb);
        tma_load(dst + 16384, &P.qkv_ld, 64, h * SEQ + qt * 128, fb);
      }
    }
  } else {
    reg_inc<232>();
    const int wg = wgid - 1, t128 = tid & 127, warp = t128 >> 5, lane = tid & 31;
    const int rloc = wg * 64 + warp * 16;
    const int r0 = rloc + (lane >> 2), t = lane & 3;
    uint32_t code = items[0];
    if (code != 0xFFFF) {
      float S[64], O[64];
      uint32_t Pr[32];
      float m0, m1, l0, l1, a0, a1;
      int slot = 0, it = 0;
      uint32_t phase = 0;
      int j = code & 15;
      int accum = 0;
      int pend = -1;
      if (wg == 1) bar_arrive(1, 256);
      mbar_wait(qfull0, 0);
      mbar_wait(full0, 0);
      bar_sync(1 + wg, 256);
      wg_fence();
      attn_qk(S, sb + A_Q_OFF + wg * 8192, sb + A_RING_OFF);
      wg_commit();
      bar_arrive(2 - wg, 256);
      wg_wait<0>();
      reg_fence(S);
      if (t128 == 0) mbar_arrive(empty0);
      slot = 1;
      attn_mask(S, r0, t);
      attn_softmax<true>(S, m0, m1, l0, l1, a0, a1);
      attn_pack(S, Pr);
      while (true) {
        const bool boundary = (j == 0);
        uint32_t ncode = code;
        if (boundary) {
          ncode = (it + 1 < K2_MAXI) ? items[it + 1] : 0xFFFFu;
          if (ncode == 0xFFFF) break;
        }
        float g0 = 0.f, g1 = 0.f;
        if (boundary) {
          const int grow = (code & 15) * 128 + r0;
          g0 = __ldg(g_gate + grow);
          g1 = __ldg(g_gate + grow + 8);
          it++;
          j = ncode & 15;
          mbar_wait(qfull0 + 8 * (it & 1), (it >> 1) & 1);
        } else {
          j--;
        }
        const int kslot = slot;
        mbar_wait(full0 + 8 * slot, phase);
        if (++slot == A_SLOTS) { slot = 0; phase ^= 1; }
        const int vslot = slot;
        bar_sync(1 + wg, 256);
        wg_fence();
        attn_qk(S, sb + A_Q_OFF + (it & 1) * A_TILE + wg * 8192, sb + A_RING_OFF + kslot * A_TILE);
        wg_commit();
        mbar_wait(full0 + 8 * slot, phase);
        if (++slot == A_SLOTS) { slot = 0; phase ^= 1; }
        reg_fence(O);
        reg_fence_u(Pr);
        wg_fence();
        attn_pv(O, Pr, sb + A_RING_OFF + vslot * A_TILE, accum);
        wg_commit();
        bar_arrive(2 - wg, 256);
        if (pend >= 0) {
          if (lane == 0) {
            bulk_wait_read<0>();
            mbar_arrive(qempty0 + 8 * pend);
          }
          pend = -1;
        }
        wg_wait<1>();
        reg_fence(S);
        if (t128 == 0) mbar_arrive(empty0 + 8 * kslot);
        if (boundary) {
          const float lo0 = l0, lo1 = l1;
          attn_mask(S, r0, t);
          attn_softmax<true>(S, m0, m1, l0, l1, a0, a1);
          wg_wait<0>();
          reg_fence(O);
          reg_fence_u(Pr);
          if (t128 == 0) mbar_arrive(empty0 + 8 * vslot);
          const int qb = (it & 1) ^ 1;
          attn_epilogue(O, lo0, lo1, g0, g1, &P.a3_st, sb + A_Q_OFF + qb * A_TILE + rloc * 128, lane,
                        1024 + (code >> 4) * 128, (code & 15) * 128 + rloc);
          pend = qb;
          code = ncode;
          accum = 0;
        } else {
          attn_softmax<false>(S, m0, m1, l0, l1, a0, a1);
          wg_wait<0>();
          reg_fence(O);
          reg_fence_u(Pr);
          if (t128 == 0) mbar_arrive(empty0 + 8 * vslot);
#pragma unroll
          for (int i = 0; i < 16; i++) {
            O[4 * i] *= a0;
            O[4 * i + 1] *= a0;
            O[4 * i + 2] *= a1;
            O[4 * i + 3] *= a1;
          }
          accum = 1;
        }
        attn_pack(S, Pr);
      }
      const int grow = (code & 15) * 128 + r0;
      const float g0 = __ldg(g_gate + grow), g1 = __ldg(g_gate + grow + 8);
      mbar_wait(full0 + 8 * slot, phase);
      bar_sync(1 + wg, 256);
      reg_fence(O);
      reg_fence_u(Pr);
      wg_fence();
      attn_pv(O, Pr, sb + A_RING_OFF + slot * A_TILE, accum);
      wg_commit();
      if (wg == 0) bar_arrive(2, 256);
      wg_wait<0>();
      reg_fence(O);
      attn_epilogue(O, l0, l1, g0, g1, &P.a3_st, sb + A_Q_OFF + (it & 1) * A_TILE + rloc * 128, lane,
                    1024 + (code >> 4) * 128, (code & 15) * 128 + rloc);
      if (lane == 0) bulk_wait<0>();
    }
  }
}

struct K3Params {
  CUtensorMap a3_ld, wo, wob, out_st;
};
constexpr int K3_NK = 40;

__global__ void __cluster_dims__(2, 1, 1) __launch_bounds__(384, 1) k3_out(const __grid_constant__ K3Params P) {
  extern __shared__ uint8_t smem_raw[];
  const uint32_t sb = (smem_u32(smem_raw) + 1023) & ~1023u;
  const uint32_t full0 = sb + G_BAR_OFF, empty0 = full0 + 8 * G_STAGES;
  const int tid = threadIdx.x, wgid = tid >> 7;
  const uint32_t rank = cluster_rank();
  const int tile = blockIdx.x >> 1, rt = tile >> 2, ct = tile & 3;
  if (tid == 0) {
    for (int s = 0; s < G_STAGES; s++) {
      mbar_init(full0 + 8 * s, 1);
      mbar_init(empty0 + 8 * s, 2);
    }
    asm volatile("fence.mbarrier_init.release.cluster;" ::: "memory");
    tma_prefetch_desc(&P.a3_ld);
    tma_prefetch_desc(&P.wo);
    tma_prefetch_desc(&P.wob);
    tma_prefetch_desc(&P.out_st);
  }
  __syncthreads();
  pdl_wait();
  if (blockIdx.x == 0 && tid < 16) g_cnt[tid] = 0;

  if (wgid == 0) {
    reg_dec<40>();
    if (tid == 0) {
      int stage = 0;
      uint32_t phase = 1;
      for (int k = 0; k < K3_NK; k++) {
        const int kg = rank * K3_NK + k;
        mbar_wait(empty0 + 8 * stage, phase);
        const uint32_t sa = sb + stage * G_STAGE_BYTES, sbb = sa + G_A_BYTES;
        const uint32_t fb = full0 + 8 * stage;
        mbar_expect_tx(fb, G_STAGE_BYTES);
        tma_load(sa, &P.a3_ld, kg * 64, rt * 128, fb);
        const CUtensorMap* mb = kg < 16 ? &P.wo : &P.wob;
        const int kr = (kg < 16 ? kg : kg - 16) * 64;
#pragma unroll
        for (int i = 0; i < 4; i++) tma_load(sbb + i * 8192, mb, ct * 256 + i * 64, kr, fb);
        if (++stage == G_STAGES) { stage = 0; phase ^= 1; }
      }
    }
  } else {
    reg_inc<232>();
    const int wg = wgid - 1, t128 = tid & 127, warp = t128 >> 5, lane = tid & 31;
    int stage = 0;
    uint32_t phase = 0;
    float acc[128];
    mbar_wait(full0, 0);
    gemm_step<true>(acc, sb, wg);
    int prev = 0;
    stage = 1;
    for (int k = 1; k < K3_NK; k++) {
      mbar_wait(full0 + 8 * stage, phase);
      gemm_step<false>(acc, sb + stage * G_STAGE_BYTES, wg);
      wg_wait<1>();
      if (t128 == 0) mbar_arrive(empty0 + 8 * prev);
      prev = stage;
      if (++stage == G_STAGES) { stage = 0; phase ^= 1; }
    }
    wg_wait<0>();
    reg_fence(acc);
    cluster_arrive();
    cluster_wait();
    const int t256 = tid - 128;
    uint32_t remote;
    asm volatile("mapa.shared::cluster.u32 %0, %1, %2;" : "=r"(remote) : "r"(sb + t256 * 16), "r"(rank ^ 1));
    if (rank == 0) {
#pragma unroll
      for (int i = 0; i < 16; i++)
        asm volatile("st.shared::cluster.v4.f32 [%0], {%1,%2,%3,%4};" ::"r"(remote + i * 4096), "f"(acc[64 + 4 * i]),
                     "f"(acc[64 + 4 * i + 1]), "f"(acc[64 + 4 * i + 2]), "f"(acc[64 + 4 * i + 3])
                     : "memory");
    } else {
#pragma unroll
      for (int i = 0; i < 16; i++) {
        asm volatile("st.shared::cluster.v4.f32 [%0], {%1,%2,%3,%4};" ::"r"(remote + i * 4096), "f"(acc[4 * i]),
                     "f"(acc[4 * i + 1]), "f"(acc[4 * i + 2]), "f"(acc[4 * i + 3])
                     : "memory");
        acc[4 * i] = acc[64 + 4 * i]; acc[4 * i + 1] = acc[64 + 4 * i + 1];
        acc[4 * i + 2] = acc[64 + 4 * i + 2]; acc[4 * i + 3] = acc[64 + 4 * i + 3];
      }
    }
    cluster_arrive();
    cluster_wait();
#pragma unroll
    for (int i = 0; i < 16; i++) {
      float4 v;
      asm volatile("ld.shared.v4.f32 {%0,%1,%2,%3}, [%4];"
                   : "=f"(v.x), "=f"(v.y), "=f"(v.z), "=f"(v.w)
                   : "r"(sb + t256 * 16 + i * 4096)
                   : "memory");
      acc[4 * i] += v.x; acc[4 * i + 1] += v.y; acc[4 * i + 2] += v.z; acc[4 * i + 3] += v.w;
    }
    const uint32_t stg = sb + G_STG_OFF + wg * 16384;
    const int y = rt * 128 + wg * 64 + warp * 16, x = ct * 256 + rank * 128;
    uint32_t pk[64];
#pragma unroll
    for (int i = 0; i < 32; i++) pk[i] = pack_bf16(acc[2 * i], acc[2 * i + 1]);
    epi_plain_box<0>(pk, &P.out_st, stg, warp, lane, x, y);
    epi_plain_box<1>(pk, &P.out_st, stg, warp, lane, x + 64, y);
    if (lane == 0) bulk_wait<0>();
  }
}

typedef CUresult (*EncodeFn)(CUtensorMap*, CUtensorMapDataType, cuuint32_t, void*, const cuuint64_t*, const cuuint64_t*,
                             const cuuint32_t*, const cuuint32_t*, CUtensorMapInterleave, CUtensorMapSwizzle,
                             CUtensorMapL2promotion, CUtensorMapFloatOOBfill);

static void make_map(EncodeFn enc, CUtensorMap* m, const void* ptr, uint64_t cols, uint64_t rows, uint32_t box_rows) {
  cuuint64_t dims[2] = {cols, rows};
  cuuint64_t strides[1] = {cols * 2};
  cuuint32_t box[2] = {64, box_rows};
  cuuint32_t es[2] = {1, 1};
  enc(m, CU_TENSOR_MAP_DATA_TYPE_BFLOAT16, 2, const_cast<void*>(ptr), dims, strides, box, es, CU_TENSOR_MAP_INTERLEAVE_NONE,
      CU_TENSOR_MAP_SWIZZLE_128B, CU_TENSOR_MAP_L2_PROMOTION_L2_256B, CU_TENSOR_MAP_FLOAT_OOB_FILL_NONE);
}

static void schedule_k1(K1Params& P) {
  uint16_t list[480];
  int n = 0;
  for (int c = 0; c < 8; c++)
    for (int r = 0; r < 8; r++) list[n++] = (T_KV << 8) | (r << 5) | c;
  for (int i = 0; i < 68; i++) list[n++] = (T_QB << 8) | ((i & 7) << 5) | (i >> 3);
  for (int c = 0; c < 4; c++)
    for (int r = 0; r < 8; r++) list[n++] = (T_QA << 8) | (r << 5) | c;
  for (int i = 68; i < 128; i++) list[n++] = (T_QB << 8) | ((i & 7) << 5) | (i >> 3);
  for (int c = 0; c < 16; c++) {
    for (int r = 0; r < 8; r++) list[n++] = (T_KB << 8) | (r << 5) | c;
    for (int r = 0; r < 8; r++) list[n++] = (T_VB << 8) | (r << 5) | c;
  }
  float load[66];
  int cnt[66];
  for (int i = 0; i < 66; i++) {
    load[i] = 0.f;
    cnt[i] = 0;
    for (int j = 0; j < K1_MAXT; j++) P.tiles[i][j] = 0xFFFF;
  }
  for (int i = 0; i < n; i++) {
    int best = 0;
    for (int c = 1; c < 66; c++)
      if (load[c] < load[best] - 1e-4f) best = c;
    const int type = list[i] >> 8;
    load[best] += (type == T_KV || type == T_QA) ? 2.3f : (type == T_QB) ? 2.05f : 1.05f;
    P.tiles[best][cnt[best]++] = list[i];
  }
}

static void schedule_k2(K2Params& P) {
  float load[132];
  int cnt[132];
  for (int i = 0; i < 132; i++) {
    load[i] = 0.f;
    cnt[i] = 0;
    for (int j = 0; j < K2_MAXI; j++) P.items[i][j] = 0xFFFF;
  }
  for (int qt = 15; qt >= 0; qt--)
    for (int h = 0; h < 32; h++) {
      int best = -1;
      for (int c = 0; c < 132; c++)
        if (cnt[c] < K2_MAXI && (best < 0 || load[c] < load[best] - 1e-4f)) best = c;
      load[best] += qt + 1 + 0.2f;
      P.items[best][cnt[best]++] = (h << 4) | qt;
    }
}

extern "C" void kernel_launch(void* const* d_in, const int* in_sizes, int n_in, void* d_out, int out_size) {
  static EncodeFn enc = nullptr;
  static void *p_qkv, *p_a3;
  if (!enc) {
    void* fn = nullptr;
    cudaDriverEntryPointQueryResult qr;
    cudaGetDriverEntryPoint("cuTensorMapEncodeTiled", &fn, cudaEnableDefault, &qr);
    enc = (EncodeFn)fn;
    cudaGetSymbolAddress(&p_qkv, g_qkv);
    cudaGetSymbolAddress(&p_a3, g_a3);
    cudaFuncSetAttribute(k1_proj, cudaFuncAttributeMaxDynamicSharedMemorySize, G_SMEM);
    cudaFuncSetAttribute(k2_attn, cudaFuncAttributeMaxDynamicSharedMemorySize, A_SMEM);
    cudaFuncSetAttribute(k3_out, cudaFuncAttributeMaxDynamicSharedMemorySize, G_SMEM);
  }
  static K1Params p1;
  static K2Params p2;
  static K3Params p3;
  make_map(enc, &p1.x, d_in[0], 1024, SEQ, 128);
  make_map(enc, &p1.ckv, d_in[5], 512, SEQ, 128);
  make_map(enc, &p1.wqkv, d_in[1], 3072, 1024, 64);
  make_map(enc, &p1.wq, d_in[6], 4096, 1024, 64);
  make_map(enc, &p1.wuk, d_in[7], 4096, 512, 64);
  make_map(enc, &p1.wuv, d_in[8], 4096, 512, 64);
  make_map(enc, &p1.qkv_st, p_qkv, 128, 96 * SEQ, 16);
  make_map(enc, &p1.a3_st, p_a3, 5120, SEQ, 16);
  p1.wphi = (const __nv_bfloat16*)d_in[2];
  p1.xin = (const __nv_bfloat16*)d_in[0];
  p1.gatew = (const __nv_bfloat16*)d_in[10];
  schedule_k1(p1);
  make_map(enc, &p2.qkv_ld, p_qkv, 128, 96 * SEQ, 128);
  p2.a3_st = p1.a3_st;
  schedule_k2(p2);
  make_map(enc, &p3.a3_ld, p_a3, 5120, SEQ, 128);
  make_map(enc, &p3.wo, d_in[3], 1024, 1024, 64);
  make_map(enc, &p3.wob, d_in[9], 1024, 4096, 64);
  make_map(enc, &p3.out_st, d_out, 1024, SEQ, 16);

  cudaStream_t st = cudaStreamPerThread;
  cudaLaunchAttribute at[1];
  at[0].id = cudaLaunchAttributeProgrammaticStreamSerialization;
  at[0].val.programmaticStreamSerializationAllowed = 1;
  cudaLaunchConfig_t cfg = {};
  cfg.blockDim = dim3(384);
  cfg.stream = st;
  cfg.gridDim = dim3(132);
  cfg.dynamicSmemBytes = G_SMEM;
  cfg.attrs = at;
  cfg.numAttrs = 0;
  cudaLaunchKernelEx(&cfg, k1_proj, p1);
  cfg.numAttrs = 1;
  cfg.dynamicSmemBytes = A_SMEM;
  cudaLaunchKernelEx(&cfg, k2_attn, p2);
  cfg.gridDim = dim3(128);
  cfg.dynamicSmemBytes = G_SMEM;
  cudaLaunchKernelEx(&cfg, k3_out, p3);
}
```

```cpp
#include <cuda_runtime.h>
#include <cuda_bf16.h>
#include <cuda.h>
#include <stdint.h>

#define PACE 400
#define ZK 56
#define PF3_TILES 5
#define PF3_N 6
#define HOLD 5
#define HOLD1 3
#define SEQ 2048
#define NHEAD 32

__device__ __align__(1024) __nv_bfloat16 g_qkv[(size_t)3 * NHEAD * SEQ * 128];
__device__ __align__(1024) __nv_bfloat16 g_o[(size_t)SEQ * 1024];
__device__ __align__(1024) uint4 g_part[NHEAD * 32 * 272];
__device__ __align__(1024) __nv_bfloat16 g_kvt[NHEAD * 40 * 64];
__device__ float g_gate[SEQ];
enum { C_PART = 0, C_KVT = 8, C_GATE = 16, C_HEAD = 32, C_O = 64, C_DONE = 80, C_ZERO = 96, C_FIN = 112, C_LINES = 113 };
__device__ __align__(128) unsigned g_cnt[C_LINES * 32];

__device__ __forceinline__ uint32_t smem_u32(const void* p) { return (uint32_t)__cvta_generic_to_shared(p); }
__device__ __forceinline__ void mbar_init(uint32_t bar, uint32_t cnt) {
  asm volatile("mbarrier.init.shared::cta.b64 [%0], %1;" ::"r"(bar), "r"(cnt) : "memory");
}
__device__ __forceinline__ void mbar_expect_tx(uint32_t bar, uint32_t bytes) {
  asm volatile("mbarrier.arrive.expect_tx.shared::cta.b64 _, [%0], %1;" ::"r"(bar), "r"(bytes) : "memory");
}
__device__ __forceinline__ void mbar_arrive(uint32_t bar) {
  asm volatile("mbarrier.arrive.shared::cta.b64 _, [%0];" ::"r"(bar) : "memory");
}
__device__ __forceinline__ void mbar_arrive_cluster(uint32_t bar, uint32_t cta) {
  asm volatile(
      "{\n.reg .b32 ra;\nmapa.shared::cluster.u32 ra, %0, %1;\n"
      "mbarrier.arrive.shared::cluster.b64 _, [ra];\n}\n" ::"r"(bar), "r"(cta)
      : "memory");
}
__device__ __forceinline__ void mbar_wait(uint32_t bar, uint32_t parity) {
  asm volatile(
      "{\n.reg .pred p, q;\n.reg .u32 n;\n.reg .u64 z;\n"
      "mbarrier.try_wait.parity.shared::cta.b64 p, [%0], %1;\n"
      "@p bra MBW_DONE;\n"
      "mov.u32 n, 0;\nmov.u64 z, 0;\n"
      "MBW_LOOP:\n"
      "add.u32 n, n, 1;\n"
      "setp.gt.u32 q, n, 0x400000;\n"
      "@q st.global.u32 [z], n;\n"
      "mbarrier.try_wait.parity.shared::cta.b64 p, [%0], %1;\n"
      "@!p bra MBW_LOOP;\n"
      "MBW_DONE:\n"
      "}\n" ::"r"(bar), "r"(parity)
      : "memory");
}
__device__ __forceinline__ bool mbar_try(uint32_t bar, uint32_t parity) {
  uint32_t ok;
  asm volatile("{\n.reg .pred p;\nmbarrier.try_wait.parity.shared::cta.b64 p, [%1], %2;\nselp.u32 %0, 1, 0, p;\n}\n"
               : "=r"(ok)
               : "r"(bar), "r"(parity)
               : "memory");
  return ok != 0;
}
__device__ __forceinline__ void tma_load(uint32_t dst, const CUtensorMap* m, int x, int y, uint32_t bar) {
  asm volatile(
      "cp.async.bulk.tensor.2d.shared::cluster.global.mbarrier::complete_tx::bytes [%0], [%1, {%3, %4}], [%2];" ::"r"(dst),
      "l"(m), "r"(bar), "r"(x), "r"(y)
      : "memory");
}
__device__ __forceinline__ void tma_load_mc(uint32_t dst, const CUtensorMap* m, int x, int y, uint32_t bar, uint16_t mask) {
  asm volatile(
      "cp.async.bulk.tensor.2d.shared::cluster.global.mbarrier::complete_tx::bytes.multicast::cluster [%0], [%1, {%3, "
      "%4}], [%2], %5;" ::"r"(dst),
      "l"(m), "r"(bar), "r"(x), "r"(y), "h"(mask)
      : "memory");
}
__device__ __forceinline__ void tma_store(const CUtensorMap* m, uint32_t src, int x, int y) {
  asm volatile("cp.async.bulk.tensor.2d.global.shared::cta.bulk_group [%0, {%2, %3}], [%1];" ::"l"(m), "r"(src), "r"(x),
               "r"(y)
               : "memory");
}
__device__ __forceinline__ void tma_prefetch_l2(const CUtensorMap* m, int x, int y) {
  asm volatile("cp.async.bulk.prefetch.tensor.2d.L2.global [%0, {%1, %2}];" ::"l"(m), "r"(x), "r"(y) : "memory");
}
__device__ __forceinline__ void prefetch_l2(const void* p, uint32_t bytes) {
  asm volatile("cp.async.bulk.prefetch.L2.global [%0], %1;" ::"l"(p), "r"(bytes) : "memory");
}
__device__ __forceinline__ void tma_prefetch_desc(const CUtensorMap* m) {
  asm volatile("prefetch.tensormap [%0];" ::"l"(m) : "memory");
}
__device__ __forceinline__ void bulk_commit() { asm volatile("cp.async.bulk.commit_group;" ::: "memory"); }
template <int N>
__device__ __forceinline__ void bulk_wait_read() {
  asm volatile("cp.async.bulk.wait_group.read %0;" ::"n"(N) : "memory");
}
template <int N>
__device__ __forceinline__ void bulk_wait() {
  asm volatile("cp.async.bulk.wait_group %0;" ::"n"(N) : "memory");
}
__device__ __forceinline__ void fence_async_smem() { asm volatile("fence.proxy.async.shared::cta;" ::: "memory"); }
__device__ __forceinline__ void wg_fence() { asm volatile("wgmma.fence.sync.aligned;" ::: "memory"); }
__device__ __forceinline__ void wg_commit() { asm volatile("wgmma.commit_group.sync.aligned;" ::: "memory"); }
template <int N>
__device__ __forceinline__ void wg_wait() {
  asm volatile("wgmma.wait_group.sync.aligned %0;" ::"n"(N) : "memory");
}
template <int N>
__device__ __forceinline__ void reg_fence(float (&d)[N]) {
#pragma unroll
  for (int i = 0; i < N; i++) asm volatile("" : "+f"(d[i])::"memory");
}
template <int N>
__device__ __forceinline__ void reg_fence_u(uint32_t (&d)[N]) {
#pragma unroll
  for (int i = 0; i < N; i++) asm volatile("" : "+r"(d[i])::"memory");
}
__device__ __forceinline__ void bar_sync(int id, int n) { asm volatile("bar.sync %0, %1;" ::"r"(id), "r"(n) : "memory"); }
__device__ __forceinline__ void bar_arrive(int id, int n) { asm volatile("bar.arrive %0, %1;" ::"r"(id), "r"(n) : "memory"); }
__device__ __forceinline__ bool elect_one() {
  uint32_t p;
  asm volatile("{\n.reg .pred P;\nelect.sync _|P, 0xffffffff;\nselp.u32 %0, 1, 0, P;\n}\n" : "=r"(p));
  return p != 0;
}
__device__ __forceinline__ uint32_t cluster_rank() {
  uint32_t r;
  asm volatile("mov.u32 %0, %%cluster_ctarank;" : "=r"(r));
  return r;
}
template <int N>
__device__ __forceinline__ void reg_dec() {
  asm volatile("setmaxnreg.dec.sync.aligned.u32 %0;" ::"n"(N));
}
template <int N>
__device__ __forceinline__ void reg_inc() {
  asm volatile("setmaxnreg.inc.sync.aligned.u32 %0;" ::"n"(N));
}
__device__ __forceinline__ uint32_t pack_bf16(float lo, float hi) {
  uint32_t r;
  asm("cvt.rn.bf16x2.f32 %0, %1, %2;" : "=r"(r) : "f"(hi), "f"(lo));
  return r;
}
__device__ __forceinline__ float ex2(float x) {
  float y;
  asm("ex2.approx.ftz.f32 %0, %1;" : "=f"(y) : "f"(x));
  return y;
}
__device__ __forceinline__ float rcp(float x) {
  float y;
  asm("rcp.approx.ftz.f32 %0, %1;" : "=f"(y) : "f"(x));
  return y;
}
__device__ __forceinline__ void stsm4(uint32_t addr, uint32_t r0, uint32_t r1, uint32_t r2, uint32_t r3) {
  asm volatile("stmatrix.sync.aligned.m8n8.x4.shared.b16 [%0], {%1, %2, %3, %4};" ::"r"(addr), "r"(r0), "r"(r1), "r"(r2),
               "r"(r3)
               : "memory");
}
__device__ __forceinline__ unsigned ld_acquire(const unsigned* p) {
  unsigned v;
  asm volatile("ld.acquire.gpu.global.u32 %0, [%1];" : "=r"(v) : "l"(p) : "memory");
  return v;
}
__device__ __forceinline__ unsigned ld_relaxed(const unsigned* p) {
  unsigned v;
  asm volatile("ld.relaxed.gpu.global.u32 %0, [%1];" : "=r"(v) : "l"(p) : "memory");
  return v;
}
__device__ __forceinline__ void spin_until(const unsigned* p, unsigned target) {
  if (ld_acquire(p) >= target) return;
  uint32_t n = 0;
  while (ld_relaxed(p) < target) {
    __nanosleep(500);
    asm volatile("{\n.reg .pred q;\n.reg .u64 z;\nmov.u64 z, 0;\nsetp.gt.u32 q, %0, 0x200000;\n@q st.global.u32 [z], %0;\n}\n" ::"r"(++n));
  }
  (void)ld_acquire(p);
}
__device__ __forceinline__ void red_release(unsigned* p, unsigned v) {
  asm volatile("red.release.gpu.global.add.u32 [%0], %1;" ::"l"(p), "r"(v) : "memory");
}
__device__ __forceinline__ uint64_t make_desc(uint32_t addr, uint32_t lbo, uint32_t sbo) {
  return (uint64_t)((addr & 0x3FFFF) >> 4) | ((uint64_t)(lbo >> 4) << 16) | ((uint64_t)(sbo >> 4) << 32) | (1ull << 62);
}

__device__ __forceinline__ void wgmma_n256_ss_tb_z(float (&d)[128], uint64_t da, uint64_t db) {
  asm volatile("{\n"
    "wgmma.mma_async.sync.aligned.m64n256k16.f32.bf16.bf16 "
    "{%0, %1, %2, %3, %4, %5, %6, %7, %8, %9, %10, %11, %12, %13, %14, %15, "
    "%16, %17, %18, %19, %20, %21, %22, %23, %24, %25, %26, %27, %28, %29, %30, %31, "
    "%32, %33, %34, %35, %36, %37, %38, %39, %40, %41, %42, %43, %44, %45, %46, %47, "
    "%48, %49, %50, %51, %52, %53, %54, %55, %56, %57, %58, %59, %60, %61, %62, %63, "
    "%64, %65, %66, %67, %68, %69, %70, %71, %72, %73, %74, %75, %76, %77, %78, %79, "
    "%80, %81, %82, %83, %84, %85, %86, %87, %88, %89, %90, %91, %92, %93, %94, %95, "
    "%96, %97, %98, %99, %100, %101, %102, %103, %104, %105, %106, %107, %108, %109, %110, %111, "
    "%112, %113, %114, %115, %116, %117, %118, %119, %120, %121, %122, %123, %124, %125, %126, %127}, "
    "%128, %129, 0, 1, 1, 0, 1;\n}\n"
    : "=f"(d[0]), "=f"(d[1]), "=f"(d[2]), "=f"(d[3]), "=f"(d[4]), "=f"(d[5]), "=f"(d[6]), "=f"(d[7]),
      "=f"(d[8]), "=f"(d[9]), "=f"(d[10]), "=f"(d[11]), "=f"(d[12]), "=f"(d[13]), "=f"(d[14]), "=f"(d[15]),
      "=f"(d[16]), "=f"(d[17]), "=f"(d[18]), "=f"(d[19]), "=f"(d[20]), "=f"(d[21]), "=f"(d[22]), "=f"(d[23]),
      "=f"(d[24]), "=f"(d[25]), "=f"(d[26]), "=f"(d[27]), "=f"(d[28]), "=f"(d[29]), "=f"(d[30]), "=f"(d[31]),
      "=f"(d[32]), "=f"(d[33]), "=f"(d[34]), "=f"(d[35]), "=f"(d[36]), "=f"(d[37]), "=f"(d[38]), "=f"(d[39]),
      "=f"(d[40]), "=f"(d[41]), "=f"(d[42]), "=f"(d[43]), "=f"(d[44]), "=f"(d[45]), "=f"(d[46]), "=f"(d[47]),
      "=f"(d[48]), "=f"(d[49]), "=f"(d[50]), "=f"(d[51]), "=f"(d[52]), "=f"(d[53]), "=f"(d[54]), "=f"(d[55]),
      "=f"(d[56]), "=f"(d[57]), "=f"(d[58]), "=f"(d[59]), "=f"(d[60]), "=f"(d[61]), "=f"(d[62]), "=f"(d[63]),
      "=f"(d[64]), "=f"(d[65]), "=f"(d[66]), "=f"(d[67]), "=f"(d[68]), "=f"(d[69]), "=f"(d[70]), "=f"(d[71]),
      "=f"(d[72]), "=f"(d[73]), "=f"(d[74]), "=f"(d[75]), "=f"(d[76]), "=f"(d[77]), "=f"(d[78]), "=f"(d[79]),
      "=f"(d[80]), "=f"(d[81]), "=f"(d[82]), "=f"(d[83]), "=f"(d[84]), "=f"(d[85]), "=f"(d[86]), "=f"(d[87]),
      "=f"(d[88]), "=f"(d[89]), "=f"(d[90]), "=f"(d[91]), "=f"(d[92]), "=f"(d[93]), "=f"(d[94]), "=f"(d[95]),
      "=f"(d[96]), "=f"(d[97]), "=f"(d[98]), "=f"(d[99]), "=f"(d[100]), "=f"(d[101]), "=f"(d[102]), "=f"(d[103]),
      "=f"(d[104]), "=f"(d[105]), "=f"(d[106]), "=f"(d[107]), "=f"(d[108]), "=f"(d[109]), "=f"(d[110]), "=f"(d[111]),
      "=f"(d[112]), "=f"(d[113]), "=f"(d[114]), "=f"(d[115]), "=f"(d[116]), "=f"(d[117]), "=f"(d[118]), "=f"(d[119]),
      "=f"(d[120]), "=f"(d[121]), "=f"(d[122]), "=f"(d[123]), "=f"(d[124]), "=f"(d[125]), "=f"(d[126]), "=f"(d[127])
    : "l"(da), "l"(db));
}
__device__ __forceinline__ void wgmma_n256_ss_tb(float (&d)[128], uint64_t da, uint64_t db) {
  asm volatile("{\n"
    "wgmma.mma_async.sync.aligned.m64n256k16.f32.bf16.bf16 "
    "{%0, %1, %2, %3, %4, %5, %6, %7, %8, %9, %10, %11, %12, %13, %14, %15, "
    "%16, %17, %18, %19, %20, %21, %22, %23, %24, %25, %26, %27, %28, %29, %30, %31, "
    "%32, %33, %34, %35, %36, %37, %38, %39, %40, %41, %42, %43, %44, %45, %46, %47, "
    "%48, %49, %50, %51, %52, %53, %54, %55, %56, %57, %58, %59, %60, %61, %62, %63, "
    "%64, %65, %66, %67, %68, %69, %70, %71, %72, %73, %74, %75, %76, %77, %78, %79, "
    "%80, %81, %82, %83, %84, %85, %86, %87, %88, %89, %90, %91, %92, %93, %94, %95, "
    "%96, %97, %98, %99, %100, %101, %102, %103, %104, %105, %106, %107, %108, %109, %110, %111, "
    "%112, %113, %114, %115, %116, %117, %118, %119, %120, %121, %122, %123, %124, %125, %126, %127}, "
    "%128, %129, 1, 1, 1, 0, 1;\n}\n"
    : "+f"(d[0]), "+f"(d[1]), "+f"(d[2]), "+f"(d[3]), "+f"(d[4]), "+f"(d[5]), "+f"(d[6]), "+f"(d[7]),
      "+f"(d[8]), "+f"(d[9]), "+f"(d[10]), "+f"(d[11]), "+f"(d[12]), "+f"(d[13]), "+f"(d[14]), "+f"(d[15]),
      "+f"(d[16]), "+f"(d[17]), "+f"(d[18]), "+f"(d[19]), "+f"(d[20]), "+f"(d[21]), "+f"(d[22]), "+f"(d[23]),
      "+f"(d[24]), "+f"(d[25]), "+f"(d[26]), "+f"(d[27]), "+f"(d[28]), "+f"(d[29]), "+f"(d[30]), "+f"(d[31]),
      "+f"(d[32]), "+f"(d[33]), "+f"(d[34]), "+f"(d[35]), "+f"(d[36]), "+f"(d[37]), "+f"(d[38]), "+f"(d[39]),
      "+f"(d[40]), "+f"(d[41]), "+f"(d[42]), "+f"(d[43]), "+f"(d[44]), "+f"(d[45]), "+f"(d[46]), "+f"(d[47]),
      "+f"(d[48]), "+f"(d[49]), "+f"(d[50]), "+f"(d[51]), "+f"(d[52]), "+f"(d[53]), "+f"(d[54]), "+f"(d[55]),
      "+f"(d[56]), "+f"(d[57]), "+f"(d[58]), "+f"(d[59]), "+f"(d[60]), "+f"(d[61]), "+f"(d[62]), "+f"(d[63]),
      "+f"(d[64]), "+f"(d[65]), "+f"(d[66]), "+f"(d[67]), "+f"(d[68]), "+f"(d[69]), "+f"(d[70]), "+f"(d[71]),
      "+f"(d[72]), "+f"(d[73]), "+f"(d[74]), "+f"(d[75]), "+f"(d[76]), "+f"(d[77]), "+f"(d[78]), "+f"(d[79]),
      "+f"(d[80]), "+f"(d[81]), "+f"(d[82]), "+f"(d[83]), "+f"(d[84]), "+f"(d[85]), "+f"(d[86]), "+f"(d[87]),
      "+f"(d[88]), "+f"(d[89]), "+f"(d[90]), "+f"(d[91]), "+f"(d[92]), "+f"(d[93]), "+f"(d[94]), "+f"(d[95]),
      "+f"(d[96]), "+f"(d[97]), "+f"(d[98]), "+f"(d[99]), "+f"(d[100]), "+f"(d[101]), "+f"(d[102]), "+f"(d[103]),
      "+f"(d[104]), "+f"(d[105]), "+f"(d[106]), "+f"(d[107]), "+f"(d[108]), "+f"(d[109]), "+f"(d[110]), "+f"(d[111]),
      "+f"(d[112]), "+f"(d[113]), "+f"(d[114]), "+f"(d[115]), "+f"(d[116]), "+f"(d[117]), "+f"(d[118]), "+f"(d[119]),
      "+f"(d[120]), "+f"(d[121]), "+f"(d[122]), "+f"(d[123]), "+f"(d[124]), "+f"(d[125]), "+f"(d[126]), "+f"(d[127])
    : "l"(da), "l"(db));
}
__device__ __forceinline__ void wgmma_n128_ss_z(float (&d)[64], uint64_t da, uint64_t db) {
  asm volatile("{\n"
    "wgmma.mma_async.sync.aligned.m64n128k16.f32.bf16.bf16 "
    "{%0, %1, %2, %3, %4, %5, %6, %7, %8, %9, %10, %11, %12, %13, %14, %15, "
    "%16, %17, %18, %19, %20, %21, %22, %23, %24, %25, %26, %27, %28, %29, %30, %31, "
    "%32, %33, %34, %35, %36, %37, %38, %39, %40, %41, %42, %43, %44, %45, %46, %47, "
    "%48, %49, %50, %51, %52, %53, %54, %55, %56, %57, %58, %59, %60, %61, %62, %63}, "
    "%64, %65, 0, 1, 1, 0, 0;\n}\n"
    : "=f"(d[0]), "=f"(d[1]), "=f"(d[2]), "=f"(d[3]), "=f"(d[4]), "=f"(d[5]), "=f"(d[6]), "=f"(d[7]),
      "=f"(d[8]), "=f"(d[9]), "=f"(d[10]), "=f"(d[11]), "=f"(d[12]), "=f"(d[13]), "=f"(d[14]), "=f"(d[15]),
      "=f"(d[16]), "=f"(d[17]), "=f"(d[18]), "=f"(d[19]), "=f"(d[20]), "=f"(d[21]), "=f"(d[22]), "=f"(d[23]),
      "=f"(d[24]), "=f"(d[25]), "=f"(d[26]), "=f"(d[27]), "=f"(d[28]), "=f"(d[29]), "=f"(d[30]), "=f"(d[31]),
      "=f"(d[32]), "=f"(d[33]), "=f"(d[34]), "=f"(d[35]), "=f"(d[36]), "=f"(d[37]), "=f"(d[38]), "=f"(d[39]),
      "=f"(d[40]), "=f"(d[41]), "=f"(d[42]), "=f"(d[43]), "=f"(d[44]), "=f"(d[45]), "=f"(d[46]), "=f"(d[47]),
      "=f"(d[48]), "=f"(d[49]), "=f"(d[50]), "=f"(d[51]), "=f"(d[52]), "=f"(d[53]), "=f"(d[54]), "=f"(d[55]),
      "=f"(d[56]), "=f"(d[57]), "=f"(d[58]), "=f"(d[59]), "=f"(d[60]), "=f"(d[61]), "=f"(d[62]), "=f"(d[63])
    : "l"(da), "l"(db));
}
__device__ __forceinline__ void wgmma_n128_ss(float (&d)[64], uint64_t da, uint64_t db) {
  asm volatile("{\n"
    "wgmma.mma_async.sync.aligned.m64n128k16.f32.bf16.bf16 "
    "{%0, %1, %2, %3, %4, %5, %6, %7, %8, %9, %10, %11, %12, %13, %14, %15, "
    "%16, %17, %18, %19, %20, %21, %22, %23, %24, %25, %26, %27, %28, %29, %30, %31, "
    "%32, %33, %34, %35, %36, %37, %38, %39, %40, %41, %42, %43, %44, %45, %46, %47, "
    "%48, %49, %50, %51, %52, %53, %54, %55, %56, %57, %58, %59, %60, %61, %62, %63}, "
    "%64, %65, 1, 1, 1, 0, 0;\n}\n"
    : "+f"(d[0]), "+f"(d[1]), "+f"(d[2]), "+f"(d[3]), "+f"(d[4]), "+f"(d[5]), "+f"(d[6]), "+f"(d[7]),
      "+f"(d[8]), "+f"(d[9]), "+f"(d[10]), "+f"(d[11]), "+f"(d[12]), "+f"(d[13]), "+f"(d[14]), "+f"(d[15]),
      "+f"(d[16]), "+f"(d[17]), "+f"(d[18]), "+f"(d[19]), "+f"(d[20]), "+f"(d[21]), "+f"(d[22]), "+f"(d[23]),
      "+f"(d[24]), "+f"(d[25]), "+f"(d[26]), "+f"(d[27]), "+f"(d[28]), "+f"(d[29]), "+f"(d[30]), "+f"(d[31]),
      "+f"(d[32]), "+f"(d[33]), "+f"(d[34]), "+f"(d[35]), "+f"(d[36]), "+f"(d[37]), "+f"(d[38]), "+f"(d[39]),
      "+f"(d[40]), "+f"(d[41]), "+f"(d[42]), "+f"(d[43]), "+f"(d[44]), "+f"(d[45]), "+f"(d[46]), "+f"(d[47]),
      "+f"(d[48]), "+f"(d[49]), "+f"(d[50]), "+f"(d[51]), "+f"(d[52]), "+f"(d[53]), "+f"(d[54]), "+f"(d[55]),
      "+f"(d[56]), "+f"(d[57]), "+f"(d[58]), "+f"(d[59]), "+f"(d[60]), "+f"(d[61]), "+f"(d[62]), "+f"(d[63])
    : "l"(da), "l"(db));
}
__device__ __forceinline__ void wgmma_n128_rs_tb_p(float (&d)[64], uint32_t a0, uint32_t a1, uint32_t a2, uint32_t a3, uint64_t db, int sd) {
  asm volatile("{\n.reg .pred p;\nsetp.ne.b32 p, %69, 0;\n"
    "wgmma.mma_async.sync.aligned.m64n128k16.f32.bf16.bf16 "
    "{%0, %1, %2, %3, %4, %5, %6, %7, %8, %9, %10, %11, %12, %13, %14, %15, "
    "%16, %17, %18, %19, %20, %21, %22, %23, %24, %25, %26, %27, %28, %29, %30, %31, "
    "%32, %33, %34, %35, %36, %37, %38, %39, %40, %41, %42, %43, %44, %45, %46, %47, "
    "%48, %49, %50, %51, %52, %53, %54, %55, %56, %57, %58, %59, %60, %61, %62, %63}, "
    "{%64, %65, %66, %67}, %68, p, 1, 1, 1;\n}\n"
    : "+f"(d[0]), "+f"(d[1]), "+f"(d[2]), "+f"(d[3]), "+f"(d[4]), "+f"(d[5]), "+f"(d[6]), "+f"(d[7]),
      "+f"(d[8]), "+f"(d[9]), "+f"(d[10]), "+f"(d[11]), "+f"(d[12]), "+f"(d[13]), "+f"(d[14]), "+f"(d[15]),
      "+f"(d[16]), "+f"(d[17]), "+f"(d[18]), "+f"(d[19]), "+f"(d[20]), "+f"(d[21]), "+f"(d[22]), "+f"(d[23]),
      "+f"(d[24]), "+f"(d[25]), "+f"(d[26]), "+f"(d[27]), "+f"(d[28]), "+f"(d[29]), "+f"(d[30]), "+f"(d[31]),
      "+f"(d[32]), "+f"(d[33]), "+f"(d[34]), "+f"(d[35]), "+f"(d[36]), "+f"(d[37]), "+f"(d[38]), "+f"(d[39]),
      "+f"(d[40]), "+f"(d[41]), "+f"(d[42]), "+f"(d[43]), "+f"(d[44]), "+f"(d[45]), "+f"(d[46]), "+f"(d[47]),
      "+f"(d[48]), "+f"(d[49]), "+f"(d[50]), "+f"(d[51]), "+f"(d[52]), "+f"(d[53]), "+f"(d[54]), "+f"(d[55]),
      "+f"(d[56]), "+f"(d[57]), "+f"(d[58]), "+f"(d[59]), "+f"(d[60]), "+f"(d[61]), "+f"(d[62]), "+f"(d[63])
    : "r"(a0), "r"(a1), "r"(a2), "r"(a3), "l"(db), "r"(sd));
}
__device__ __forceinline__ void wgmma_n128_rs_tb(float (&d)[64], uint32_t a0, uint32_t a1, uint32_t a2, uint32_t a3, uint64_t db) {
  asm volatile("{\n"
    "wgmma.mma_async.sync.aligned.m64n128k16.f32.bf16.bf16 "
    "{%0, %1, %2, %3, %4, %5, %6, %7, %8, %9, %10, %11, %12, %13, %14, %15, "
    "%16, %17, %18, %19, %20, %21, %22, %23, %24, %25, %26, %27, %28, %29, %30, %31, "
    "%32, %33, %34, %35, %36, %37, %38, %39, %40, %41, %42, %43, %44, %45, %46, %47, "
    "%48, %49, %50, %51, %52, %53, %54, %55, %56, %57, %58, %59, %60, %61, %62, %63}, "
    "{%64, %65, %66, %67}, %68, 1, 1, 1, 1;\n}\n"
    : "+f"(d[0]), "+f"(d[1]), "+f"(d[2]), "+f"(d[3]), "+f"(d[4]), "+f"(d[5]), "+f"(d[6]), "+f"(d[7]),
      "+f"(d[8]), "+f"(d[9]), "+f"(d[10]), "+f"(d[11]), "+f"(d[12]), "+f"(d[13]), "+f"(d[14]), "+f"(d[15]),
      "+f"(d[16]), "+f"(d[17]), "+f"(d[18]), "+f"(d[19]), "+f"(d[20]), "+f"(d[21]), "+f"(d[22]), "+f"(d[23]),
      "+f"(d[24]), "+f"(d[25]), "+f"(d[26]), "+f"(d[27]), "+f"(d[28]), "+f"(d[29]), "+f"(d[30]), "+f"(d[31]),
      "+f"(d[32]), "+f"(d[33]), "+f"(d[34]), "+f"(d[35]), "+f"(d[36]), "+f"(d[37]), "+f"(d[38]), "+f"(d[39]),
      "+f"(d[40]), "+f"(d[41]), "+f"(d[42]), "+f"(d[43]), "+f"(d[44]), "+f"(d[45]), "+f"(d[46]), "+f"(d[47]),
      "+f"(d[48]), "+f"(d[49]), "+f"(d[50]), "+f"(d[51]), "+f"(d[52]), "+f"(d[53]), "+f"(d[54]), "+f"(d[55]),
      "+f"(d[56]), "+f"(d[57]), "+f"(d[58]), "+f"(d[59]), "+f"(d[60]), "+f"(d[61]), "+f"(d[62]), "+f"(d[63])
    : "r"(a0), "r"(a1), "r"(a2), "r"(a3), "l"(db));
}
__device__ __forceinline__ void wgmma_n32_ss_tb_z(float (&d)[16], uint64_t da, uint64_t db) {
  asm volatile("{\n"
    "wgmma.mma_async.sync.aligned.m64n32k16.f32.bf16.bf16 "
    "{%0, %1, %2, %3, %4, %5, %6, %7, %8, %9, %10, %11, %12, %13, %14, %15}, "
    "%16, %17, 0, 1, 1, 0, 1;\n}\n"
    : "=f"(d[0]), "=f"(d[1]), "=f"(d[2]), "=f"(d[3]), "=f"(d[4]), "=f"(d[5]), "=f"(d[6]), "=f"(d[7]),
      "=f"(d[8]), "=f"(d[9]), "=f"(d[10]), "=f"(d[11]), "=f"(d[12]), "=f"(d[13]), "=f"(d[14]), "=f"(d[15])
    : "l"(da), "l"(db));
}
__device__ __forceinline__ void wgmma_n32_ss_tb(float (&d)[16], uint64_t da, uint64_t db) {
  asm volatile("{\n"
    "wgmma.mma_async.sync.aligned.m64n32k16.f32.bf16.bf16 "
    "{%0, %1, %2, %3, %4, %5, %6, %7, %8, %9, %10, %11, %12, %13, %14, %15}, "
    "%16, %17, 1, 1, 1, 0, 1;\n}\n"
    : "+f"(d[0]), "+f"(d[1]), "+f"(d[2]), "+f"(d[3]), "+f"(d[4]), "+f"(d[5]), "+f"(d[6]), "+f"(d[7]),
      "+f"(d[8]), "+f"(d[9]), "+f"(d[10]), "+f"(d[11]), "+f"(d[12]), "+f"(d[13]), "+f"(d[14]), "+f"(d[15])
    : "l"(da), "l"(db));
}
__device__ __forceinline__ void wgmma_n32_ss_tatb_z(float (&d)[16], uint64_t da, uint64_t db) {
  asm volatile("{\n"
    "wgmma.mma_async.sync.aligned.m64n32k16.f32.bf16.bf16 "
    "{%0, %1, %2, %3, %4, %5, %6, %7, %8, %9, %10, %11, %12, %13, %14, %15}, "
    "%16, %17, 0, 1, 1, 1, 1;\n}\n"
    : "=f"(d[0]), "=f"(d[1]), "=f"(d[2]), "=f"(d[3]), "=f"(d[4]), "=f"(d[5]), "=f"(d[6]), "=f"(d[7]),
      "=f"(d[8]), "=f"(d[9]), "=f"(d[10]), "=f"(d[11]), "=f"(d[12]), "=f"(d[13]), "=f"(d[14]), "=f"(d[15])
    : "l"(da), "l"(db));
}
__device__ __forceinline__ void wgmma_n32_ss_tatb(float (&d)[16], uint64_t da, uint64_t db) {
  asm volatile("{\n"
    "wgmma.mma_async.sync.aligned.m64n32k16.f32.bf16.bf16 "
    "{%0, %1, %2, %3, %4, %5, %6, %7, %8, %9, %10, %11, %12, %13, %14, %15}, "
    "%16, %17, 1, 1, 1, 1, 1;\n}\n"
    : "+f"(d[0]), "+f"(d[1]), "+f"(d[2]), "+f"(d[3]), "+f"(d[4]), "+f"(d[5]), "+f"(d[6]), "+f"(d[7]),
      "+f"(d[8]), "+f"(d[9]), "+f"(d[10]), "+f"(d[11]), "+f"(d[12]), "+f"(d[13]), "+f"(d[14]), "+f"(d[15])
    : "l"(da), "l"(db));
}
__device__ __forceinline__ void wgmma_n8_ss_ta_z(float (&d)[4], uint64_t da, uint64_t db) {
  asm volatile("{\n"
    "wgmma.mma_async.sync.aligned.m64n8k16.f32.bf16.bf16 "
    "{%0, %1, %2, %3}, "
    "%4, %5, 0, 1, 1, 1, 0;\n}\n"
    : "=f"(d[0]), "=f"(d[1]), "=f"(d[2]), "=f"(d[3])
    : "l"(da), "l"(db));
}
__device__ __forceinline__ void wgmma_n8_ss_ta(float (&d)[4], uint64_t da, uint64_t db) {
  asm volatile("{\n"
    "wgmma.mma_async.sync.aligned.m64n8k16.f32.bf16.bf16 "
    "{%0, %1, %2, %3}, "
    "%4, %5, 1, 1, 1, 1, 0;\n}\n"
    : "+f"(d[0]), "+f"(d[1]), "+f"(d[2]), "+f"(d[3])
    : "l"(da), "l"(db));
}
__device__ __forceinline__ void wgmma_n40_rs_z(float (&d)[20], uint32_t a0, uint32_t a1, uint32_t a2, uint32_t a3, uint64_t db) {
  asm volatile("{\n"
    "wgmma.mma_async.sync.aligned.m64n40k16.f32.bf16.bf16 "
    "{%0, %1, %2, %3, %4, %5, %6, %7, %8, %9, %10, %11, %12, %13, %14, %15, "
    "%16, %17, %18, %19}, "
    "{%20, %21, %22, %23}, %24, 0, 1, 1, 0;\n}\n"
    : "=f"(d[0]), "=f"(d[1]), "=f"(d[2]), "=f"(d[3]), "=f"(d[4]), "=f"(d[5]), "=f"(d[6]), "=f"(d[7]),
      "=f"(d[8]), "=f"(d[9]), "=f"(d[10]), "=f"(d[11]), "=f"(d[12]), "=f"(d[13]), "=f"(d[14]), "=f"(d[15]),
      "=f"(d[16]), "=f"(d[17]), "=f"(d[18]), "=f"(d[19])
    : "r"(a0), "r"(a1), "r"(a2), "r"(a3), "l"(db));
}
__device__ __forceinline__ void wgmma_n40_rs(float (&d)[20], uint32_t a0, uint32_t a1, uint32_t a2, uint32_t a3, uint64_t db) {
  asm volatile("{\n"
    "wgmma.mma_async.sync.aligned.m64n40k16.f32.bf16.bf16 "
    "{%0, %1, %2, %3, %4, %5, %6, %7, %8, %9, %10, %11, %12, %13, %14, %15, "
    "%16, %17, %18, %19}, "
    "{%20, %21, %22, %23}, %24, 1, 1, 1, 0;\n}\n"
    : "+f"(d[0]), "+f"(d[1]), "+f"(d[2]), "+f"(d[3]), "+f"(d[4]), "+f"(d[5]), "+f"(d[6]), "+f"(d[7]),
      "+f"(d[8]), "+f"(d[9]), "+f"(d[10]), "+f"(d[11]), "+f"(d[12]), "+f"(d[13]), "+f"(d[14]), "+f"(d[15]),
      "+f"(d[16]), "+f"(d[17]), "+f"(d[18]), "+f"(d[19])
    : "r"(a0), "r"(a1), "r"(a2), "r"(a3), "l"(db));
}
__device__ __forceinline__ void wgmma_n64_ss_z(float (&d)[64], uint64_t da, uint64_t db) {
  asm volatile("{\n"
    "wgmma.mma_async.sync.aligned.m64n64k16.f32.bf16.bf16 "
    "{%0, %1, %2, %3, %4, %5, %6, %7, %8, %9, %10, %11, %12, %13, %14, %15, "
    "%16, %17, %18, %19, %20, %21, %22, %23, %24, %25, %26, %27, %28, %29, %30, %31}, "
    "%32, %33, 0, 1, 1, 0, 0;\n}\n"
    : "=f"(d[0]), "=f"(d[1]), "=f"(d[2]), "=f"(d[3]), "=f"(d[4]), "=f"(d[5]), "=f"(d[6]), "=f"(d[7]),
      "=f"(d[8]), "=f"(d[9]), "=f"(d[10]), "=f"(d[11]), "=f"(d[12]), "=f"(d[13]), "=f"(d[14]), "=f"(d[15]),
      "=f"(d[16]), "=f"(d[17]), "=f"(d[18]), "=f"(d[19]), "=f"(d[20]), "=f"(d[21]), "=f"(d[22]), "=f"(d[23]),
      "=f"(d[24]), "=f"(d[25]), "=f"(d[26]), "=f"(d[27]), "=f"(d[28]), "=f"(d[29]), "=f"(d[30]), "=f"(d[31])
    : "l"(da), "l"(db));
}
__device__ __forceinline__ void wgmma_n64_ss(float (&d)[64], uint64_t da, uint64_t db) {
  asm volatile("{\n"
    "wgmma.mma_async.sync.aligned.m64n64k16.f32.bf16.bf16 "
    "{%0, %1, %2, %3, %4, %5, %6, %7, %8, %9, %10, %11, %12, %13, %14, %15, "
    "%16, %17, %18, %19, %20, %21, %22, %23, %24, %25, %26, %27, %28, %29, %30, %31}, "
    "%32, %33, 1, 1, 1, 0, 0;\n}\n"
    : "+f"(d[0]), "+f"(d[1]), "+f"(d[2]), "+f"(d[3]), "+f"(d[4]), "+f"(d[5]), "+f"(d[6]), "+f"(d[7]),
      "+f"(d[8]), "+f"(d[9]), "+f"(d[10]), "+f"(d[11]), "+f"(d[12]), "+f"(d[13]), "+f"(d[14]), "+f"(d[15]),
      "+f"(d[16]), "+f"(d[17]), "+f"(d[18]), "+f"(d[19]), "+f"(d[20]), "+f"(d[21]), "+f"(d[22]), "+f"(d[23]),
      "+f"(d[24]), "+f"(d[25]), "+f"(d[26]), "+f"(d[27]), "+f"(d[28]), "+f"(d[29]), "+f"(d[30]), "+f"(d[31])
    : "l"(da), "l"(db));
}


constexpr int G_STAGES = 8;
constexpr int G_STAGE_BYTES = 24576;
constexpr int G_WPHI_OFF = 6 * G_STAGE_BYTES;
constexpr int G_STG_OFF = G_WPHI_OFF + 16384;
constexpr int A_SLOTS = 5, O_STAGES = 8;
constexpr int A_TILE = 32768;
constexpr int A_RING_OFF = A_TILE;
constexpr int A_Q_STRIDE = 6 * A_TILE;
constexpr int G_ONES_OFF = 7 * A_TILE;
constexpr int BAR_OFF = G_ONES_OFF + 256;
constexpr int B_GFULL = BAR_OFF, B_GEMPTY = B_GFULL + 8 * G_STAGES, B_SFULL = B_GEMPTY + 8 * G_STAGES, B_SFREE = B_SFULL + 8,
              B_WFULL = B_SFREE + 8, B_KFULL = B_WFULL + 8, B_KGO = B_KFULL + 8, B_P1DRAIN = B_KGO + 8, B_P1DONE = B_P1DRAIN + 8,
              B_AFULL = B_P1DONE + 8, B_AEMPTY = B_AFULL + 8 * A_SLOTS, B_QFULL = B_AEMPTY + 8 * A_SLOTS,
              B_QEMPTY = B_QFULL + 16, B_OFULL = B_QEMPTY + 16, B_P2DONE = B_OFULL + 16, B_ZGO = B_P2DONE + 8,
              B_OFULLS = B_ZGO + 8,
              B_OEMPTYS = B_OFULLS + 8 * O_STAGES, B_PROG = B_OEMPTYS + 8 * O_STAGES, B_PIN = B_PROG + 8, B_END = B_PIN + 8;
constexpr int SMEM_BYTES = B_END + 1024;
static_assert(SMEM_BYTES <= 232448 && G_STG_OFF + 65536 == 7 * A_TILE, "smem");

enum { T_KV = 0, T_QA = 1, T_QB = 2, T_KB = 3, T_VB = 4, T_OUT = 5 };
constexpr int K1_MAXT = 12, K2_MAXI = 8, K3_NK = 80;
struct Params {
  CUtensorMap x, ckv, wqkv, wq, wuk, wuv, wphi, qkv_st, o_st, qkv_ld, o_ld, wo, wob, out_st;
  const void *ckv_p, *wo_p, *wob_p;
  const __nv_bfloat16* xin;
  const __nv_bfloat16* gatew;
  uint16_t tiles[66][K1_MAXT];
  uint16_t items[66][K2_MAXI];
  uint8_t rot1[66], skip2[66];
  uint8_t k3[8][40];
  __nv_bfloat16* out;
  uint32_t zero;
};
static const uint16_t c_tiles[66][K1_MAXT] = {
  {0x300, 0x0, 0x304, 0x100, 0x204, 0x308, 0x24D, 0xFFFF, 0xFFFF, 0xFFFF, 0xFFFF, 0xFFFF},
  {0x320, 0x20, 0x324, 0x120, 0x224, 0x328, 0x26D, 0xFFFF, 0xFFFF, 0xFFFF, 0xFFFF, 0xFFFF},
  {0x340, 0x40, 0x344, 0x140, 0x244, 0x348, 0x28D, 0xFFFF, 0xFFFF, 0xFFFF, 0xFFFF, 0xFFFF},
  {0x360, 0x60, 0x364, 0x160, 0x264, 0x368, 0x2AD, 0xFFFF, 0xFFFF, 0xFFFF, 0xFFFF, 0xFFFF},
  {0x380, 0x80, 0x384, 0x180, 0x284, 0x388, 0x2CD, 0xFFFF, 0xFFFF, 0xFFFF, 0xFFFF, 0xFFFF},
  {0x3A0, 0xA0, 0x3A4, 0x1A0, 0x2A4, 0x3A8, 0x2ED, 0xFFFF, 0xFFFF, 0xFFFF, 0xFFFF, 0xFFFF},
  {0x3C0, 0xC0, 0x3C4, 0x1C0, 0x2C4, 0x3C8, 0x20E, 0xFFFF, 0xFFFF, 0xFFFF, 0xFFFF, 0xFFFF},
  {0x3E0, 0xE0, 0x3E4, 0x1E0, 0x2E4, 0x3E8, 0x22E, 0xFFFF, 0xFFFF, 0xFFFF, 0xFFFF, 0xFFFF},
  {0x400, 0x1, 0x404, 0x101, 0x205, 0x408, 0x24E, 0xFFFF, 0xFFFF, 0xFFFF, 0xFFFF, 0xFFFF},
  {0x420, 0x21, 0x424, 0x121, 0x225, 0x428, 0x26E, 0xFFFF, 0xFFFF, 0xFFFF, 0xFFFF, 0xFFFF},
  {0x440, 0x41, 0x444, 0x141, 0x245, 0x448, 0x28E, 0xFFFF, 0xFFFF, 0xFFFF, 0xFFFF, 0xFFFF},
  {0x460, 0x61, 0x464, 0x161, 0x265, 0x468, 0x2AE, 0xFFFF, 0xFFFF, 0xFFFF, 0xFFFF, 0xFFFF},
  {0x480, 0x81, 0x484, 0x181, 0x285, 0x488, 0x2CE, 0xFFFF, 0xFFFF, 0xFFFF, 0xFFFF, 0xFFFF},
  {0x4A0, 0xA1, 0x4A4, 0x1A1, 0x2A5, 0x4A8, 0x2EE, 0xFFFF, 0xFFFF, 0xFFFF, 0xFFFF, 0xFFFF},
  {0x4C0, 0xC1, 0x4C4, 0x1C1, 0x2C5, 0x4C8, 0x20F, 0xFFFF, 0xFFFF, 0xFFFF, 0xFFFF, 0xFFFF},
  {0x4E0, 0xE1, 0x4E4, 0x1E1, 0x2E5, 0x4E8, 0x22F, 0xFFFF, 0xFFFF, 0xFFFF, 0xFFFF, 0xFFFF},
  {0x301, 0x2, 0x305, 0x102, 0x206, 0x309, 0x24F, 0xFFFF, 0xFFFF, 0xFFFF, 0xFFFF, 0xFFFF},
  {0x321, 0x22, 0x325, 0x122, 0x226, 0x329, 0x26F, 0xFFFF, 0xFFFF, 0xFFFF, 0xFFFF, 0xFFFF},
  {0x341, 0x42, 0x345, 0x142, 0x246, 0x349, 0x28F, 0xFFFF, 0xFFFF, 0xFFFF, 0xFFFF, 0xFFFF},
  {0x361, 0x62, 0x365, 0x162, 0x266, 0x369, 0x2AF, 0xFFFF, 0xFFFF, 0xFFFF, 0xFFFF, 0xFFFF},
  {0x381, 0x82, 0x385, 0x182, 0x286, 0x389, 0x2CF, 0xFFFF, 0xFFFF, 0xFFFF, 0xFFFF, 0xFFFF},
  {0x3A1, 0xA2, 0x3A5, 0x1A2, 0x2A6, 0x3A9, 0x2EF, 0xFFFF, 0xFFFF, 0xFFFF, 0xFFFF, 0xFFFF},
  {0x3C1, 0xC2, 0x3C5, 0x1C2, 0x2C6, 0x3C9, 0x30C, 0x30E, 0xFFFF, 0xFFFF, 0xFFFF, 0xFFFF},
  {0x3E1, 0xE2, 0x3E5, 0x1E2, 0x2E6, 0x3E9, 0x32C, 0x32E, 0xFFFF, 0xFFFF, 0xFFFF, 0xFFFF},
  {0x401, 0x3, 0x405, 0x103, 0x207, 0x409, 0x34C, 0x34E, 0xFFFF, 0xFFFF, 0xFFFF, 0xFFFF},
  {0x421, 0x23, 0x425, 0x123, 0x227, 0x429, 0x36C, 0x36E, 0xFFFF, 0xFFFF, 0xFFFF, 0xFFFF},
  {0x441, 0x43, 0x445, 0x143, 0x247, 0x449, 0x38C, 0x38E, 0xFFFF, 0xFFFF, 0xFFFF, 0xFFFF},
  {0x461, 0x63, 0x465, 0x163, 0x267, 0x469, 0x3AC, 0x3AE, 0xFFFF, 0xFFFF, 0xFFFF, 0xFFFF},
  {0x481, 0x83, 0x485, 0x183, 0x287, 0x489, 0x3CC, 0x3CE, 0xFFFF, 0xFFFF, 0xFFFF, 0xFFFF},
  {0x4A1, 0xA3, 0x4A5, 0x1A3, 0x2A7, 0x4A9, 0x3EC, 0x3EE, 0xFFFF, 0xFFFF, 0xFFFF, 0xFFFF},
  {0x4C1, 0xC3, 0x4C5, 0x1C3, 0x2C7, 0x4C9, 0x40C, 0x40E, 0xFFFF, 0xFFFF, 0xFFFF, 0xFFFF},
  {0x4E1, 0xE3, 0x4E5, 0x1E3, 0x2E7, 0x4E9, 0x42C, 0x42E, 0xFFFF, 0xFFFF, 0xFFFF, 0xFFFF},
  {0x302, 0x4, 0x306, 0x104, 0x208, 0x30A, 0x44C, 0x44E, 0xFFFF, 0xFFFF, 0xFFFF, 0xFFFF},
  {0x322, 0x24, 0x326, 0x124, 0x228, 0x32A, 0x46C, 0x46E, 0xFFFF, 0xFFFF, 0xFFFF, 0xFFFF},
  {0x342, 0x44, 0x346, 0x144, 0x248, 0x34A, 0x48C, 0x48E, 0xFFFF, 0xFFFF, 0xFFFF, 0xFFFF},
  {0x362, 0x64, 0x366, 0x164, 0x268, 0x36A, 0x4AC, 0x4AE, 0xFFFF, 0xFFFF, 0xFFFF, 0xFFFF},
  {0x382, 0x84, 0x386, 0x184, 0x288, 0x38A, 0x4CC, 0x4CE, 0xFFFF, 0xFFFF, 0xFFFF, 0xFFFF},
  {0x3A2, 0xA4, 0x3A6, 0x1A4, 0x2A8, 0x3AA, 0x4EC, 0x4EE, 0xFFFF, 0xFFFF, 0xFFFF, 0xFFFF},
  {0x3C2, 0xC4, 0x3C6, 0x1C4, 0x2C8, 0x3CA, 0x30D, 0x30F, 0xFFFF, 0xFFFF, 0xFFFF, 0xFFFF},
  {0x3E2, 0xE4, 0x3E6, 0x1E4, 0x2E8, 0x3EA, 0x32D, 0x32F, 0xFFFF, 0xFFFF, 0xFFFF, 0xFFFF},
  {0x402, 0x5, 0x406, 0x105, 0x209, 0x40A, 0x34D, 0x34F, 0xFFFF, 0xFFFF, 0xFFFF, 0xFFFF},
  {0x422, 0x25, 0x426, 0x125, 0x229, 0x42A, 0x36D, 0x36F, 0xFFFF, 0xFFFF, 0xFFFF, 0xFFFF},
  {0x442, 0x45, 0x446, 0x145, 0x249, 0x44A, 0x38D, 0x38F, 0xFFFF, 0xFFFF, 0xFFFF, 0xFFFF},
  {0x462, 0x65, 0x466, 0x165, 0x269, 0x46A, 0x3AD, 0x3AF, 0xFFFF, 0xFFFF, 0xFFFF, 0xFFFF},
  {0x482, 0x85, 0x486, 0x185, 0x289, 0x48A, 0x3CD, 0x3CF, 0xFFFF, 0xFFFF, 0xFFFF, 0xFFFF},
  {0x4A2, 0xA5, 0x4A6, 0x1A5, 0x2A9, 0x4AA, 0x3ED, 0x3EF, 0xFFFF, 0xFFFF, 0xFFFF, 0xFFFF},
  {0x4C2, 0xC5, 0x4C6, 0x1C5, 0x2C9, 0x4CA, 0x40D, 0x40F, 0xFFFF, 0xFFFF, 0xFFFF, 0xFFFF},
  {0x4E2, 0xE5, 0x4E6, 0x1E5, 0x2E9, 0x4EA, 0x42D, 0x42F, 0xFFFF, 0xFFFF, 0xFFFF, 0xFFFF},
  {0x303, 0x6, 0x307, 0x106, 0x20A, 0x30B, 0x44D, 0x44F, 0xFFFF, 0xFFFF, 0xFFFF, 0xFFFF},
  {0x323, 0x26, 0x327, 0x126, 0x22A, 0x32B, 0x46D, 0x46F, 0xFFFF, 0xFFFF, 0xFFFF, 0xFFFF},
  {0x343, 0x46, 0x347, 0x146, 0x24A, 0x34B, 0x48D, 0x48F, 0xFFFF, 0xFFFF, 0xFFFF, 0xFFFF},
  {0x363, 0x66, 0x367, 0x166, 0x26A, 0x36B, 0x4AD, 0x4AF, 0xFFFF, 0xFFFF, 0xFFFF, 0xFFFF},
  {0x383, 0x86, 0x387, 0x186, 0x28A, 0x38B, 0x4CD, 0x4CF, 0xFFFF, 0xFFFF, 0xFFFF, 0xFFFF},
  {0x3A3, 0xA6, 0x3A7, 0x1A6, 0x2AA, 0x3AB, 0x4ED, 0x4EF, 0xFFFF, 0xFFFF, 0xFFFF, 0xFFFF},
  {0x3C3, 0xC6, 0x3C7, 0x1C6, 0x2CA, 0x3CB, 0xFFFF, 0xFFFF, 0xFFFF, 0xFFFF, 0xFFFF, 0xFFFF},
  {0x3E3, 0xE6, 0x3E7, 0x1E6, 0x2EA, 0x3EB, 0xFFFF, 0xFFFF, 0xFFFF, 0xFFFF, 0xFFFF, 0xFFFF},
  {0x403, 0x7, 0x407, 0x107, 0x20B, 0x40B, 0xFFFF, 0xFFFF, 0xFFFF, 0xFFFF, 0xFFFF, 0xFFFF},
  {0x423, 0x27, 0x427, 0x127, 0x22B, 0x42B, 0xFFFF, 0xFFFF, 0xFFFF, 0xFFFF, 0xFFFF, 0xFFFF},
  {0x443, 0x47, 0x447, 0x147, 0x24B, 0x44B, 0xFFFF, 0xFFFF, 0xFFFF, 0xFFFF, 0xFFFF, 0xFFFF},
  {0x463, 0x67, 0x467, 0x167, 0x26B, 0x46B, 0xFFFF, 0xFFFF, 0xFFFF, 0xFFFF, 0xFFFF, 0xFFFF},
  {0x483, 0x87, 0x487, 0x187, 0x28B, 0x48B, 0xFFFF, 0xFFFF, 0xFFFF, 0xFFFF, 0xFFFF, 0xFFFF},
  {0x4A3, 0xA7, 0x4A7, 0x1A7, 0x2AB, 0x4AB, 0xFFFF, 0xFFFF, 0xFFFF, 0xFFFF, 0xFFFF, 0xFFFF},
  {0x4C3, 0xC7, 0x4C7, 0x1C7, 0x2CB, 0x4CB, 0xFFFF, 0xFFFF, 0xFFFF, 0xFFFF, 0xFFFF, 0xFFFF},
  {0x4E3, 0xE7, 0x4E7, 0x1E7, 0x2EB, 0x4EB, 0xFFFF, 0xFFFF, 0xFFFF, 0xFFFF, 0xFFFF, 0xFFFF},
  {0x20C, 0x24C, 0x28C, 0x2CC, 0x20D, 0xFFFF, 0xFFFF, 0xFFFF, 0xFFFF, 0xFFFF, 0xFFFF, 0xFFFF},
  {0x22C, 0x26C, 0x2AC, 0x2EC, 0x22D, 0xFFFF, 0xFFFF, 0xFFFF, 0xFFFF, 0xFFFF, 0xFFFF, 0xFFFF},
};
static const uint16_t c_items[66][K2_MAXI] = {
  {0x123, 0x1C7, 0x54, 0xFFFF, 0xFFFF, 0xFFFF, 0xFFFF, 0xFFFF},
  {0x105, 0xC7, 0x2, 0xFFFF, 0xFFFF, 0xFFFF, 0xFFFF, 0xFFFF},
  {0x116, 0x1E1, 0xB6, 0x1E0, 0xFFFF, 0xFFFF, 0xFFFF, 0xFFFF},
  {0x115, 0x1C1, 0xC2, 0xB1, 0x22, 0xFFFF, 0xFFFF, 0xFFFF},
  {0x133, 0x1C6, 0x84, 0x1F0, 0xFFFF, 0xFFFF, 0xFFFF, 0xFFFF},
  {0x125, 0xF6, 0x72, 0xF0, 0xFFFF, 0xFFFF, 0xFFFF, 0xFFFF},
  {0x112, 0x1A5, 0x47, 0xFFFF, 0xFFFF, 0xFFFF, 0xFFFF, 0xFFFF},
  {0x122, 0x196, 0x96, 0xFFFF, 0xFFFF, 0xFFFF, 0xFFFF, 0xFFFF},
  {0x126, 0xF4, 0x24, 0xFFFF, 0xFFFF, 0xFFFF, 0xFFFF, 0xFFFF},
  {0x136, 0xC4, 0x34, 0xFFFF, 0xFFFF, 0xFFFF, 0xFFFF, 0xFFFF},
  {0x101, 0x182, 0x1D3, 0xD1, 0x83, 0x120, 0xFFFF, 0xFFFF},
  {0x104, 0x1A3, 0x57, 0xFFFF, 0xFFFF, 0xFFFF, 0xFFFF, 0xFFFF},
  {0x100, 0x184, 0x1E5, 0x93, 0xC0, 0xFFFF, 0xFFFF, 0xFFFF},
  {0x114, 0x1F6, 0x73, 0xD0, 0xFFFF, 0xFFFF, 0xFFFF, 0xFFFF},
  {0x124, 0x1B3, 0x27, 0xFFFF, 0xFFFF, 0xFFFF, 0xFFFF, 0xFFFF},
  {0x135, 0x1F5, 0x43, 0xA0, 0xFFFF, 0xFFFF, 0xFFFF, 0xFFFF},
  {0x145, 0x1C4, 0x25, 0xFFFF, 0xFFFF, 0xFFFF, 0xFFFF, 0xFFFF},
  {0x143, 0x1D7, 0x53, 0xB0, 0xFFFF, 0xFFFF, 0xFFFF, 0xFFFF},
  {0x132, 0x1B7, 0x94, 0x80, 0xFFFF, 0xFFFF, 0xFFFF, 0xFFFF},
  {0x146, 0x1D2, 0x76, 0xFFFF, 0xFFFF, 0xFFFF, 0xFFFF, 0xFFFF},
  {0x153, 0x1E7, 0x4, 0xFFFF, 0xFFFF, 0xFFFF, 0xFFFF, 0xFFFF},
  {0x142, 0x1A6, 0x95, 0x90, 0xFFFF, 0xFFFF, 0xFFFF, 0xFFFF},
  {0x155, 0x1D4, 0x74, 0x70, 0xFFFF, 0xFFFF, 0xFFFF, 0xFFFF},
  {0x107, 0xD7, 0x150, 0xFFFF, 0xFFFF, 0xFFFF, 0xFFFF, 0xFFFF},
  {0x152, 0x181, 0x1B1, 0xF1, 0x86, 0xFFFF, 0xFFFF, 0xFFFF},
  {0x156, 0x1F1, 0x37, 0xFFFF, 0xFFFF, 0xFFFF, 0xFFFF, 0xFFFF},
  {0x163, 0x1A1, 0xF3, 0xA1, 0x82, 0x130, 0xFFFF, 0xFFFF},
  {0x111, 0x194, 0xF2, 0xA2, 0x32, 0xFFFF, 0xFFFF, 0xFFFF},
  {0x134, 0x1F7, 0x42, 0x40, 0xFFFF, 0xFFFF, 0xFFFF, 0xFFFF},
  {0x117, 0xA7, 0x160, 0xFFFF, 0xFFFF, 0xFFFF, 0xFFFF, 0xFFFF},
  {0x121, 0x187, 0x46, 0xFFFF, 0xFFFF, 0xFFFF, 0xFFFF, 0xFFFF},
  {0x131, 0x197, 0x56, 0xFFFF, 0xFFFF, 0xFFFF, 0xFFFF, 0xFFFF},
  {0x165, 0x1E4, 0x35, 0xFFFF, 0xFFFF, 0xFFFF, 0xFFFF, 0xFFFF},
  {0x175, 0x1F4, 0x5, 0xFFFF, 0xFFFF, 0xFFFF, 0xFFFF, 0xFFFF},
  {0x127, 0xB7, 0x170, 0xFFFF, 0xFFFF, 0xFFFF, 0xFFFF, 0xFFFF},
  {0x137, 0x87, 0x180, 0xFFFF, 0xFFFF, 0xFFFF, 0xFFFF, 0xFFFF},
  {0x147, 0x97, 0x190, 0xFFFF, 0xFFFF, 0xFFFF, 0xFFFF, 0xFFFF},
  {0x144, 0x1D5, 0x44, 0x50, 0xFFFF, 0xFFFF, 0xFFFF, 0xFFFF},
  {0x157, 0xD6, 0x11, 0xFFFF, 0xFFFF, 0xFFFF, 0xFFFF, 0xFFFF},
  {0x166, 0xC6, 0x51, 0x20, 0xFFFF, 0xFFFF, 0xFFFF, 0xFFFF},
  {0x154, 0xF7, 0x13, 0xFFFF, 0xFFFF, 0xFFFF, 0xFFFF, 0xFFFF},
  {0x167, 0xA5, 0x12, 0xFFFF, 0xFFFF, 0xFFFF, 0xFFFF, 0xFFFF},
  {0x141, 0x195, 0xC3, 0x81, 0x31, 0xFFFF, 0xFFFF, 0xFFFF},
  {0x164, 0x1B4, 0x75, 0x30, 0xFFFF, 0xFFFF, 0xFFFF, 0xFFFF},
  {0x151, 0x171, 0x1A2, 0xD4, 0x33, 0xFFFF, 0xFFFF, 0xFFFF},
  {0xE5, 0xF5, 0x14, 0xFFFF, 0xFFFF, 0xFFFF, 0xFFFF, 0xFFFF},
  {0x162, 0x1B5, 0x7, 0xFFFF, 0xFFFF, 0xFFFF, 0xFFFF, 0xFFFF},
  {0x174, 0x1C3, 0x17, 0xFFFF, 0xFFFF, 0xFFFF, 0xFFFF, 0xFFFF},
  {0x172, 0x1B6, 0x26, 0xFFFF, 0xFFFF, 0xFFFF, 0xFFFF, 0xFFFF},
  {0x177, 0x77, 0x1A0, 0xFFFF, 0xFFFF, 0xFFFF, 0xFFFF, 0xFFFF},
  {0x173, 0x1D6, 0x15, 0xFFFF, 0xFFFF, 0xFFFF, 0xFFFF, 0xFFFF},
  {0xE4, 0x1B2, 0xC1, 0xB3, 0x1, 0xFFFF, 0xFFFF, 0xFFFF},
  {0x176, 0x1E2, 0x45, 0x0, 0xFFFF, 0xFFFF, 0xFFFF, 0xFFFF},
  {0xE6, 0x1F2, 0x36, 0xFFFF, 0xFFFF, 0xFFFF, 0xFFFF, 0xFFFF},
  {0x65, 0x1A7, 0x55, 0xFFFF, 0xFFFF, 0xFFFF, 0xFFFF, 0xFFFF},
  {0x67, 0x1A4, 0xB5, 0x1B0, 0xFFFF, 0xFFFF, 0xFFFF, 0xFFFF},
  {0x63, 0x161, 0x191, 0x1E3, 0xD2, 0x3, 0xFFFF, 0xFFFF},
  {0x61, 0x102, 0x183, 0xC5, 0x23, 0xFFFF, 0xFFFF, 0xFFFF},
  {0x62, 0xE3, 0x1E6, 0xB2, 0x21, 0xFFFF, 0xFFFF, 0xFFFF},
  {0x66, 0x1C5, 0x85, 0x1C0, 0xFFFF, 0xFFFF, 0xFFFF, 0xFFFF},
  {0x64, 0x186, 0xA6, 0x1D0, 0xFFFF, 0xFFFF, 0xFFFF, 0xFFFF},
  {0x60, 0xE2, 0x185, 0xE1, 0xA3, 0x91, 0x110, 0xFFFF},
  {0x71, 0x103, 0x192, 0x1D1, 0xD3, 0x92, 0x140, 0xFFFF},
  {0x41, 0x113, 0x193, 0xD5, 0x52, 0xFFFF, 0xFFFF, 0xFFFF},
  {0xE0, 0x106, 0x1C2, 0xA4, 0x6, 0x10, 0xFFFF, 0xFFFF},
  {0xE7, 0x1F3, 0xB4, 0x16, 0xFFFF, 0xFFFF, 0xFFFF, 0xFFFF},
};
static const uint8_t c_k3[8][40] = {
  {0, 2, 14, 24, 5, 7, 26, 28, 30, 32, 34, 36, 38, 23, 21, 19, 17, 12, 10, 8, 1, 3, 22, 4, 6, 25, 27, 29, 31, 33, 35, 37, 39, 20, 18, 16, 15, 13, 11, 9},
  {0, 2, 12, 14, 16, 18, 20, 22, 38, 36, 34, 32, 30, 28, 26, 24, 5, 7, 10, 8, 1, 3, 15, 17, 19, 21, 23, 39, 37, 35, 33, 31, 29, 27, 25, 4, 6, 13, 11, 9},
  {0, 2, 14, 16, 18, 20, 22, 38, 36, 34, 32, 30, 28, 26, 24, 5, 7, 12, 10, 8, 1, 3, 17, 19, 21, 23, 39, 37, 35, 33, 31, 29, 27, 25, 4, 6, 15, 13, 11, 9},
  {0, 2, 14, 19, 21, 23, 39, 37, 35, 33, 31, 29, 27, 25, 4, 6, 17, 12, 10, 8, 1, 3, 16, 18, 20, 22, 38, 36, 34, 32, 30, 28, 26, 24, 5, 7, 15, 13, 11, 9},
  {0, 2, 14, 18, 20, 22, 38, 36, 34, 32, 30, 28, 26, 24, 5, 7, 17, 12, 10, 8, 1, 3, 19, 21, 23, 39, 37, 35, 33, 31, 29, 27, 25, 4, 6, 16, 15, 13, 11, 9},
  {0, 2, 14, 19, 21, 23, 39, 37, 35, 33, 31, 29, 27, 25, 4, 6, 17, 12, 10, 8, 1, 3, 16, 18, 20, 22, 38, 36, 34, 32, 30, 28, 26, 24, 5, 7, 15, 13, 11, 9},
  {0, 2, 14, 21, 23, 39, 37, 35, 33, 31, 29, 27, 25, 4, 6, 19, 17, 12, 10, 8, 1, 3, 18, 20, 22, 38, 36, 34, 32, 30, 28, 26, 24, 5, 7, 16, 15, 13, 11, 9},
  {0, 2, 15, 17, 19, 21, 23, 39, 37, 35, 33, 31, 29, 27, 25, 4, 6, 12, 10, 8, 1, 3, 14, 16, 18, 20, 22, 38, 36, 34, 32, 30, 28, 26, 24, 5, 7, 13, 11, 9},
};
static const uint8_t c_rot1[66] = {4, 4, 4, 4, 4, 4, 4, 4, 4, 4, 4, 4, 4, 4, 4, 4, 4, 4, 4, 4, 4, 4, 4, 4, 4, 4, 4, 4, 4, 4, 4, 4, 4, 4, 4, 4, 4, 4, 4, 4, 4, 4, 4, 4, 4, 4, 4, 4, 4, 4, 4, 4, 4, 4, 4, 4, 4, 4, 4, 4, 4, 4, 4, 4, 0, 0};


struct K1Ctx {
  uint32_t sb, rank;
  int wg, t128;
  uint32_t st, lim, phases;
  uint32_t pend, npend;
  uint32_t alo, blo, alo0;
  uint32_t full, empty;
};
__device__ __forceinline__ void k1_wait(K1Ctx& c) { mbar_wait(c.full + c.st, c.phases & 1); }
template <bool FIRST, bool WAIT = true>
__device__ __forceinline__ void k1_big(float (&acc)[128], K1Ctx& c) {
  if (WAIT) k1_wait(c);
  const uint64_t da = c.alo | (0x40000040ull << 32), db = c.blo | (0x40000040ull << 32);
  wg_fence();
  if (FIRST)
    wgmma_n256_ss_tb_z(acc, da, db);
  else
    wgmma_n256_ss_tb(acc, da, db);
  wgmma_n256_ss_tb(acc, da | 2, db | 128);
  wg_commit();
  c.pend |= c.st << c.npend;
  c.npend += 8;
  const bool odd = c.st & 8;
  c.alo += odd ? 3068 : 4;
  c.blo += odd ? 2048 : 1024;
  c.st += 8;
  c.phases = __funnelshift_r(c.phases ^ 1, c.phases ^ 1, 4);
  if (c.st >= c.lim) {
    if (c.st != 64) c.phases = __funnelshift_r(c.phases, c.phases, 8);
    c.blo -= c.alo - c.alo0;
    c.alo = c.alo0;
    c.st = 0;
  }
}
__device__ __forceinline__ void k1_rel(K1Ctx& c) {
  if (c.t128 < 2) mbar_arrive_cluster(c.empty + (c.pend & 255), c.t128);
  c.pend >>= 8;
  c.npend -= 8;
}

template <int r>
__device__ __forceinline__ void dual_softmax(const float (&p)[16], uint32_t (&phi)[16]) {
  const float L2E = 1.4426950408889634f;
  {
    float mx = fmaxf(p[2 * r], p[2 * r + 1]), mn = fminf(p[2 * r], p[2 * r + 1]);
#pragma unroll
    for (int j = 1; j < 4; j++) {
      mx = fmaxf(mx, fmaxf(p[4 * j + 2 * r], p[4 * j + 2 * r + 1]));
      mn = fminf(mn, fminf(p[4 * j + 2 * r], p[4 * j + 2 * r + 1]));
    }
    mx = fmaxf(mx, __shfl_xor_sync(0xffffffffu, mx, 1));
    mn = fminf(mn, __shfl_xor_sync(0xffffffffu, mn, 1));
    mx = fmaxf(mx, __shfl_xor_sync(0xffffffffu, mx, 2));
    mn = fminf(mn, __shfl_xor_sync(0xffffffffu, mn, 2));
    const float mxs = mx * L2E, mns = mn * L2E;
    float ep[8], en[8], sp = 0.f, sn = 0.f;
#pragma unroll
    for (int j = 0; j < 4; j++)
#pragma unroll
      for (int c = 0; c < 2; c++) {
        const float v = p[4 * j + 2 * r + c];
        ep[2 * j + c] = ex2(fmaf(v, L2E, -mxs));
        en[2 * j + c] = ex2(fmaf(v, -L2E, mns));
        sp += ep[2 * j + c];
        sn += en[2 * j + c];
      }
    sp += __shfl_xor_sync(0xffffffffu, sp, 1);
    sn += __shfl_xor_sync(0xffffffffu, sn, 1);
    sp += __shfl_xor_sync(0xffffffffu, sp, 2);
    sn += __shfl_xor_sync(0xffffffffu, sn, 2);
    const float ip = rcp(sp), in = rcp(sn);
#pragma unroll
    for (int j = 0; j < 4; j++) {
      phi[2 * j + r] = pack_bf16(ep[2 * j] * ip, ep[2 * j + 1] * ip);
      phi[8 + 2 * j + r] = pack_bf16(en[2 * j] * in, en[2 * j + 1] * in);
    }
  }
}
__device__ __forceinline__ void mma_p(float (&p)[16], uint32_t a, uint32_t w) {
  const uint64_t da = make_desc(a, 16, 1024);
  const uint64_t db = (uint64_t)((w & 0x3FFFF) >> 4) | ((uint64_t)(512 >> 4) << 16) | ((uint64_t)(512 >> 4) << 32) | (2ull << 62);
  wgmma_n32_ss_tb_z(p, da, db);
  wgmma_n32_ss_tb(p, da + 2, db + 64);
}
__device__ __forceinline__ void store_phi(uint32_t row_addr, const uint32_t (&phi)[16], int lane) {
#pragma unroll
  for (int c = 0; c < 4; c++)
    stsm4(row_addr + (((uint32_t)(2 * c + (lane >> 4)) ^ (lane & 7)) << 4), phi[4 * c], phi[4 * c + 1], phi[4 * c + 2],
          phi[4 * c + 3]);
}
template <int N>
__device__ __forceinline__ void k1_next(float (&acc)[128], K1Ctx& c) {
  wg_wait<N>();
  k1_rel(c);
  k1_big<false>(acc, c);
}
__device__ __forceinline__ void mma_kv(float (&d)[16], float (&z)[4], uint32_t phi, uint32_t v, uint32_t ones, int wg) {
  fence_async_smem();
  bar_sync(1 + wg, 128);
  const uint64_t da = make_desc(phi, 16384, 1024), db = make_desc(v, 16384, 1024);
  const uint64_t dones = (uint64_t)((ones & 0x3FFFF) >> 4) | ((uint64_t)(128 >> 4) << 16) | ((uint64_t)(128 >> 4) << 32);
  wg_fence();
  wgmma_n32_ss_tatb_z(d, da, db);
  wgmma_n8_ss_ta_z(z, da, dones);
#pragma unroll
  for (int kk = 1; kk < 4; kk++) {
    wgmma_n32_ss_tatb(d, da + kk * 128, db + kk * 128);
    wgmma_n8_ss_ta(z, da + kk * 128, dones);
  }
  wg_commit();
}
__device__ __forceinline__ void store_part(uint4* dst, const uint32_t (&d)[8], float zv, int t128) {
  dst[t128] = make_uint4(d[0], d[1], d[2], d[3]);
  dst[128 + t128] = make_uint4(d[4], d[5], d[6], d[7]);
  if ((t128 & 3) < 2) ((float*)(dst + 256))[(t128 >> 5) * 16 + (t128 & 1) * 8 + ((t128 & 31) >> 2)] = zv;
}
__device__ __forceinline__ void k1_kv_pair(float (&acc)[128], K1Ctx& c, uint32_t pcode, int idx) {
  const int lane = c.t128 & 31, warp = c.t128 >> 5;
  const uint32_t kbox = c.sb + G_STG_OFF + idx * 32768 + c.wg * 8192, wphi = c.sb + G_WPHI_OFF + idx * 4096;
  const uint32_t row = kbox + (warp * 16 + (lane & 15)) * 128;
  uint4* dst = g_part + (((pcode & 31) * 4 + idx * 2) * 32 + ((pcode >> 5) & 7) * 4 + c.rank * 2 + c.wg) * 272;
  float p0[16], p1[16], d[16], z[4];
  uint32_t phi[16], db[8];
  wg_fence();
  mma_p(p0, kbox, wphi);
  mma_p(p1, kbox + 64, wphi + 2048);
  wg_commit();
  k1_big<false>(acc, c);
  k1_next<2>(acc, c);
  wg_wait<2>();
  reg_fence(p0);
  reg_fence(p1);
  dual_softmax<0>(p0, phi);
  k1_next<1>(acc, c);
  dual_softmax<1>(p0, phi);
  store_phi(row, phi, lane);
  k1_next<1>(acc, c);
  mma_kv(d, z, kbox, kbox + 16384, c.sb + G_ONES_OFF, c.wg);
  dual_softmax<0>(p1, phi);
  k1_next<2>(acc, c);
  dual_softmax<1>(p1, phi);
  wg_wait<1>();
  k1_rel(c);
  reg_fence(d);
  reg_fence(z);
  bar_sync(1 + c.wg, 128);
  store_phi(row, phi, lane);
  k1_big<false>(acc, c);
#pragma unroll
  for (int i = 0; i < 8; i++) db[i] = pack_bf16(d[2 * i], d[2 * i + 1]);
  const float zv = (lane & 1) ? z[2] : z[0];
  mma_kv(d, z, kbox, kbox + 16384 + 64, c.sb + G_ONES_OFF, c.wg);
  store_part(dst, db, zv, c.t128);
  k1_next<2>(acc, c);
  wg_wait<1>();
  k1_rel(c);
  reg_fence(d);
  reg_fence(z);
#pragma unroll
  for (int i = 0; i < 8; i++) db[i] = pack_bf16(d[2 * i], d[2 * i + 1]);
  store_part(dst + 32 * 272, db, (lane & 1) ? z[2] : z[0], c.t128);
}
__device__ __forceinline__ void k1_q_head(float (&acc)[128], K1Ctx& c, int idx, float g0, float g1) {
  const int lane = c.t128 & 31, warp = c.t128 >> 5;
  const uint32_t stg = c.sb + G_STG_OFF, qbox = stg + 32768 + (idx >> 1) * 16384 + c.wg * 8192;
  float p0[16], o[20];
  uint32_t phi[16];
  wg_fence();
  mma_p(p0, qbox + (idx & 1) * 64, c.sb + G_WPHI_OFF + idx * 2048);
  wg_commit();
  k1_big<false>(acc, c);
  k1_next<2>(acc, c);
  wg_wait<2>();
  reg_fence(p0);
  dual_softmax<0>(p0, phi);
  k1_next<1>(acc, c);
  dual_softmax<1>(p0, phi);
  k1_next<1>(acc, c);
  reg_fence_u(phi);
  const uint64_t db = make_desc(stg + idx * 5120, 16, 1024);
  wg_fence();
  wgmma_n40_rs_z(o, phi[0], phi[1], phi[2], phi[3], db);
#pragma unroll
  for (int kk = 1; kk < 4; kk++) wgmma_n40_rs(o, phi[4 * kk], phi[4 * kk + 1], phi[4 * kk + 2], phi[4 * kk + 3], db + kk * 2);
  wg_commit();
  k1_next<2>(acc, c);
  wg_wait<1>();
  k1_rel(c);
  reg_fence(o);
  const float s0 = g0 * rcp(o[16] + 1e-6f), s1 = g1 * rcp(o[18] + 1e-6f);
  const uint32_t ra = qbox + (warp * 16 + (lane & 15)) * 128;
#pragma unroll
  for (int i = 0; i < 2; i++)
    stsm4(ra + (((uint32_t)((idx & 1) * 4 + 2 * i + (lane >> 4)) ^ (lane & 7)) << 4),
          pack_bf16(o[8 * i] * s0, o[8 * i + 1] * s0), pack_bf16(o[8 * i + 2] * s1, o[8 * i + 3] * s1),
          pack_bf16(o[8 * i + 4] * s0, o[8 * i + 5] * s0), pack_bf16(o[8 * i + 6] * s1, o[8 * i + 7] * s1));
}

__device__ __forceinline__ void helper_gate(const Params& P, int rowbase, int hw, int lane) {
#pragma unroll 1
  for (int rr = hw; rr < 8; rr += 2) {
    float acc[2] = {0.f, 0.f};
    const int row0 = rowbase + rr * 2;
#pragma unroll
    for (int i = 0; i < 4; i++) {
      const uint4 gv = __ldg((const uint4*)P.gatew + i * 32 + lane);
      const uint32_t gs[4] = {gv.x, gv.y, gv.z, gv.w};
#pragma unroll
      for (int r = 0; r < 2; r++) {
        const uint4 xv = __ldg((const uint4*)(P.xin + (size_t)(row0 + r) * 1024) + i * 32 + lane);
        const uint32_t xs[4] = {xv.x, xv.y, xv.z, xv.w};
#pragma unroll
        for (int c = 0; c < 4; c++) {
          acc[r] = fmaf(__uint_as_float(xs[c] << 16), __uint_as_float(gs[c] << 16), acc[r]);
          acc[r] = fmaf(__uint_as_float(xs[c] & 0xffff0000u), __uint_as_float(gs[c] & 0xffff0000u), acc[r]);
        }
      }
    }
#pragma unroll
    for (int r = 0; r < 2; r++) {
#pragma unroll
      for (int o = 16; o > 0; o >>= 1) acc[r] += __shfl_xor_sync(0xffffffffu, acc[r], o);
      if (lane == 0) g_gate[row0 + r] = rcp(1.f + ex2(-acc[r] * 1.4426950408889634f));
    }
  }
}

__device__ __forceinline__ void helper_reduce(int b, int hw, int lane) {
  const int h = b >> 2, q = b & 3;
  const uint4* src = g_part + h * 32 * 272;
  __nv_bfloat16* dst = g_kvt + h * 2560;
  const int g = lane >> 2, t = lane & 3;
  float s[8];
#pragma unroll
  for (int e = 0; e < 8; e++) s[e] = 0.f;
#pragma unroll 8
  for (int p = 0; p < 32; p++) {
    const uint4 v = __ldcg(src + p * 272 + hw * 128 + q * 32 + lane);
    const uint32_t w[4] = {v.x, v.y, v.z, v.w};
#pragma unroll
    for (int e = 0; e < 4; e++) {
      s[2 * e] += __uint_as_float(w[e] << 16);
      s[2 * e + 1] += __uint_as_float(w[e] & 0xffff0000u);
    }
  }
#pragma unroll
  for (int e = 0; e < 8; e++) {
    const int i = 2 * hw + (e >> 2), r = (e >> 1) & 1, d = 8 * i + 2 * t + (e & 1);
    dst[d * 64 + (((2 * q + r) ^ (d & 7)) << 3) + g] = __float2bfloat16(s[e]);
  }
  {
    const float4* zp = (const float4*)(src + lane * 272 + 256) + q * 4 + hw * 2;
    const float4 a = __ldcg(zp), c = __ldcg(zp + 1);
    float z[8] = {a.x, a.y, a.z, a.w, c.x, c.y, c.z, c.w};
#pragma unroll
    for (int st = 0; st < 3; st++) {
      const int m = 16 >> st, n = 4 >> st;
      const bool up = lane & m;
#pragma unroll
      for (int e = 0; e < n; e++) {
        const float send = up ? z[e] : z[e + n], keep = up ? z[e + n] : z[e];
        z[e] = keep + __shfl_xor_sync(0xffffffffu, send, m);
      }
    }
    z[0] += __shfl_xor_sync(0xffffffffu, z[0], 1);
    z[0] += __shfl_xor_sync(0xffffffffu, z[0], 2);
    const __nv_bfloat16 zb = __float2bfloat16(z[0]);
#pragma unroll
    for (int n = 0; n < 2; n++) {
      const int d = 32 + 2 * t + n;
      dst[d * 64 + (((2 * q + hw) ^ (d & 7)) << 3) + g] = zb;
    }
  }
}

__device__ __forceinline__ int qkv_row(int half, int y) { return (y & ~(SEQ - 1)) + half * SEQ + y; }
__device__ __forceinline__ void pace(long long t0, int cycles) {
  while (clock64() - t0 < cycles) __nanosleep(64);
}

__device__ __forceinline__ void attn_qk(float (&S)[64], uint64_t da, uint64_t db) {
  wgmma_n128_ss_z(S, da, db);
#pragma unroll
  for (int kk = 1; kk < 8; kk++) {
    const int off = (kk >> 2) * 1024 + (kk & 3) * 2;
    wgmma_n128_ss(S, da + off, db + off);
  }
}
__device__ __forceinline__ void attn_qk_half(float (&S)[64], uint64_t da, uint64_t db) {
  wgmma_n64_ss_z(S, da, db);
#pragma unroll
  for (int kk = 1; kk < 8; kk++) {
    const int off = (kk >> 2) * 1024 + (kk & 3) * 2;
    wgmma_n64_ss(S, da + off, db + off);
  }
}
template <int NK>
__device__ __forceinline__ void attn_pv(float (&O)[64], const uint32_t (&Pr)[32], uint64_t db, int accum) {
  wgmma_n128_rs_tb_p(O, Pr[0], Pr[1], Pr[2], Pr[3], db, accum);
#pragma unroll
  for (int kk = 1; kk < NK; kk++)
    wgmma_n128_rs_tb(O, Pr[4 * kk], Pr[4 * kk + 1], Pr[4 * kk + 2], Pr[4 * kk + 3], db + kk * 128);
}
constexpr float A_SCALE = 0.08838834764831845f * 1.4426950408889634f;

template <int J0>
__device__ __forceinline__ void attn_mask(float (&S)[64], int r0, int t) {
#pragma unroll
  for (int j = J0; j < J0 + 8; j++) {
    const int c = 8 * j + 2 * t;
    if (c > r0) S[4 * j] = -INFINITY;
    if (c + 1 > r0) S[4 * j + 1] = -INFINITY;
    if (c > r0 + 8) S[4 * j + 2] = -INFINITY;
    if (c + 1 > r0 + 8) S[4 * j + 3] = -INFINITY;
  }
}
template <int R, int NJ>
__device__ __forceinline__ float attn_rowmax(const float (&S)[64]) {
  float x = fmaxf(S[2 * R], S[2 * R + 1]), y = fmaxf(S[4 + 2 * R], S[4 + 2 * R + 1]);
#pragma unroll
  for (int j = 2; j < NJ; j += 2) {
    x = fmaxf(x, fmaxf(S[4 * j + 2 * R], S[4 * j + 2 * R + 1]));
    y = fmaxf(y, fmaxf(S[4 * j + 4 + 2 * R], S[4 * j + 4 + 2 * R + 1]));
  }
  x = fmaxf(x, y);
  x = fmaxf(x, __shfl_xor_sync(0xffffffffu, x, 1));
  return fmaxf(x, __shfl_xor_sync(0xffffffffu, x, 2));
}
template <int R, int NJ>
__device__ __forceinline__ float attn_rowexp(float (&S)[64], float negc) {
  float s = 0.f, u = 0.f;
#pragma unroll
  for (int j = 0; j < NJ; j++) {
    S[4 * j + 2 * R] = ex2(fmaf(S[4 * j + 2 * R], A_SCALE, negc));
    S[4 * j + 2 * R + 1] = ex2(fmaf(S[4 * j + 2 * R + 1], A_SCALE, negc));
    s += S[4 * j + 2 * R];
    u += S[4 * j + 2 * R + 1];
  }
  return s + u;
}
__device__ __forceinline__ void sched_pin(float v, uint32_t addr) {
  asm volatile("{\n.reg .pred p;\nsetp.gt.f32 p, %0, 0f7E000000;\n@p st.shared.u32 [%1], %1;\n}\n" ::"f"(v), "r"(addr) : "memory");
}
__device__ __forceinline__ void attn_epilogue(const float (&O)[64], float l0, float l1, float g0, float g1, uint32_t qrows,
                                              uint32_t ofull, int lane) {
  l0 += __shfl_xor_sync(0xffffffffu, l0, 1);
  l1 += __shfl_xor_sync(0xffffffffu, l1, 1);
  l0 += __shfl_xor_sync(0xffffffffu, l0, 2);
  l1 += __shfl_xor_sync(0xffffffffu, l1, 2);
  const float i0 = (1.f - g0) * rcp(l0), i1 = (1.f - g1) * rcp(l1);
  const uint32_t row = (lane & 7) + ((lane >> 3) & 1) * 8;
#pragma unroll
  for (int i = 0; i < 8; i++) {
    const int j = 2 * i;
    const uint32_t ch = (uint32_t)(2 * (i & 3) + (lane >> 4)) ^ (lane & 7);
    stsm4(qrows + (i >> 2) * 16384 + row * 128 + ch * 16, pack_bf16(O[4 * j] * i0, O[4 * j + 1] * i0),
          pack_bf16(O[4 * j + 2] * i1, O[4 * j + 3] * i1), pack_bf16(O[4 * j + 4] * i0, O[4 * j + 5] * i0),
          pack_bf16(O[4 * j + 6] * i1, O[4 * j + 7] * i1));
  }
  fence_async_smem();
  __syncwarp();
  if (lane == 0) mbar_arrive(ofull);
}

__device__ __forceinline__ void attn_release(uint32_t bar, int t128) {
  if (t128 < 2) mbar_arrive_cluster(bar, t128);
}
__device__ __forceinline__ void attn_softmax_lazy(float (&S)[64], float (&O)[64], uint32_t (&Pr)[32], float& m0, float& m1,
                                                  float& l0, float& l1, uint32_t vrel, int t128, uint32_t pin,
                                                  uint32_t rt_zero, uint64_t qdesc, uint64_t kdesc, int wg) {
  float s0 = attn_rowexp<0, 16>(S, -m0 * A_SCALE);
  sched_pin(s0, pin);
  wg_wait<0>();
  reg_fence(O);
  reg_fence_u(Pr);
  attn_release(vrel, t128);
  const float nc1 = __uint_as_float(__float_as_uint(-m1 * A_SCALE) | (__float_as_uint(O[0]) & rt_zero));
  float s1 = attn_rowexp<1, 16>(S, nc1);
#pragma unroll
  for (int i = 0; i < 32; i++) Pr[i] = pack_bf16(S[2 * i], S[2 * i + 1]);
  uint32_t bad;
  asm volatile("{\n.reg .pred p, q;\nsetp.gtu.f32 p, %1, 0f4B800000;\nbar.red.or.pred q, %2, 128, p;\nselp.u32 %0, 1, 0, q;\n}\n"
               : "=r"(bad)
               : "f"(s0 + s1), "r"(1 + wg)
               : "memory");
  if (__any_sync(0xffffffffu, bad)) {
    wg_fence();
    attn_qk(S, qdesc, kdesc);
    wg_commit();
    wg_wait<0>();
    reg_fence(S);
    const float x0 = fmaxf(m0, attn_rowmax<0, 16>(S)), x1 = fmaxf(m1, attn_rowmax<1, 16>(S));
    const float a0 = ex2((m0 - x0) * A_SCALE), a1 = ex2((m1 - x1) * A_SCALE);
    m0 = x0;
    m1 = x1;
    l0 *= a0;
    l1 *= a1;
#pragma unroll
    for (int i = 0; i < 16; i++) {
      O[4 * i] *= a0;
      O[4 * i + 1] *= a0;
      O[4 * i + 2] *= a1;
      O[4 * i + 3] *= a1;
    }
    s0 = attn_rowexp<0, 16>(S, -m0 * A_SCALE);
    s1 = attn_rowexp<1, 16>(S, -m1 * A_SCALE);
#pragma unroll
    for (int i = 0; i < 32; i++) Pr[i] = pack_bf16(S[2 * i], S[2 * i + 1]);
  }
  l0 += s0;
  l1 += s1;
}

struct AttnCtx {
  uint64_t kdesc0, vdesc0;
  uint32_t full0, empty0, pin, zero;
  int slot;
  uint32_t phase;
  int wg, lane, t128;
};
struct AttnOut {
  float l0, l1, g0, g1;
  uint32_t stage, ofull;
};
__device__ __forceinline__ void attn_next(AttnCtx& c) {
  if (++c.slot == A_SLOTS) { c.slot = 0; c.phase ^= 1; }
}
template <bool UP, bool PV>
__device__ __forceinline__ void attn_step_first(float (&S)[64], float (&O)[64], uint32_t (&Pr)[32], float& m0, float& m1,
                                                float& l0, float& l1, AttnCtx& c, uint64_t qdesc, bool have_prev, int accum,
                                                int r0) {
  const int ks = c.slot;
  attn_next(c);
  int vs = ks;
  bar_sync(5 + PV, 256);
  wg_fence();
  if (UP)
    attn_qk_half(S, qdesc, c.kdesc0 + ks * 2048);
  else
    attn_qk(S, qdesc, c.kdesc0 + ks * 2048);
  wg_commit();
  if (!PV) bar_arrive(6, 256);
  if (!PV || have_prev) {
    vs = c.slot;
    mbar_wait(c.full0 + 8 * c.slot, c.phase);
    attn_next(c);
  }
  if (PV) {
    reg_fence(O);
    reg_fence_u(Pr);
    wg_fence();
    attn_pv<8>(O, Pr, c.vdesc0 + vs * 2048, accum);
    wg_commit();
    bar_arrive(5, 256);
  } else {
    attn_release(c.empty0 + 8 * vs, c.t128);
  }
  mbar_wait(c.full0 + 8 * c.slot, c.phase);
  wg_wait<PV>();
  constexpr int NJ = UP ? 8 : 16;
#pragma unroll
  for (int i = 0; i < 4 * NJ; i++) asm volatile("" : "+f"(S[i])::"memory");
  if (!PV || have_prev) attn_release(c.empty0 + 8 * ks, c.t128);
  attn_mask<UP ? 0 : 8>(S, r0, c.lane & 3);
  m0 = attn_rowmax<0, NJ>(S);
  m1 = attn_rowmax<1, NJ>(S);
  l0 = attn_rowexp<0, NJ>(S, -m0 * A_SCALE);
  l1 = attn_rowexp<1, NJ>(S, -m1 * A_SCALE);
  if (PV) {
    sched_pin(l0 + l1, c.pin);
    wg_wait<0>();
    reg_fence(O);
    reg_fence_u(Pr);
    attn_release(c.empty0 + 8 * vs, c.t128);
  }
#pragma unroll
  for (int i = 0; i < 32; i++) Pr[i] = i < 2 * NJ ? pack_bf16(S[2 * i], S[2 * i + 1]) : 0u;
}
__device__ __forceinline__ void attn_step(float (&S)[64], float (&O)[64], uint32_t (&Pr)[32], float& m0, float& m1, float& l0,
                                          float& l1, AttnCtx& c, uint64_t qdesc, int accum, bool epi, const AttnOut& o) {
  const int ks = c.slot;
  const int vs = (ks == A_SLOTS - 1) ? 0 : ks + 1;
  const uint32_t vph = c.phase ^ (vs == 0);
  c.slot = (vs == A_SLOTS - 1) ? 0 : vs + 1;
  c.phase = vph ^ (c.slot == 0);
  const bool vok = mbar_try(c.full0 + 8 * vs, vph);
  bar_sync(5 + c.wg, 256);
  wg_fence();
  attn_qk(S, qdesc, c.kdesc0 + ks * 2048);
  wg_commit();
  if (epi) attn_epilogue(O, o.l0, o.l1, o.g0, o.g1, o.stage, o.ofull, c.lane);
  if (!vok) mbar_wait(c.full0 + 8 * vs, vph);
  reg_fence(O);
  reg_fence_u(Pr);
  wg_fence();
  attn_pv<8>(O, Pr, c.vdesc0 + vs * 2048, accum);
  wg_commit();
  bar_arrive(6 - c.wg, 256);
  const bool kok = mbar_try(c.full0 + 8 * c.slot, c.phase);
  wg_wait<1>();
  reg_fence(S);
  attn_softmax_lazy(S, O, Pr, m0, m1, l0, l1, c.empty0 + 8 * vs, c.t128, c.pin, c.zero, qdesc, c.kdesc0 + ks * 2048, c.wg);
  attn_release(c.empty0 + 8 * ks, c.t128);
  if (!kok) mbar_wait(c.full0 + 8 * c.slot, c.phase);
}

__global__ void __cluster_dims__(2, 1, 1) __launch_bounds__(384, 1) gated_mix_kernel(const __grid_constant__ Params P) {
  extern __shared__ uint8_t smem_raw[];
  const uint32_t sb = (smem_u32(smem_raw) + 1023) & ~1023u;
  const uint32_t stg = sb + G_STG_OFF;
  const int tid = threadIdx.x, warpid = __shfl_sync(0xffffffffu, tid >> 5, 0), wgid = warpid >> 2;
  const uint32_t rank = cluster_rank();
  const int cl = blockIdx.x >> 1;
  const uint16_t* tiles = P.tiles[cl];
  const uint16_t* items = P.items[cl];
  const bool has_p3 = cl < 64;
  const int rt3 = (cl >> 3) * 2 + rank, ct3 = cl & 3, kh3 = (cl >> 2) & 1;
  const uint8_t* k3 = P.k3[(cl >> 3) & 7] + kh3 * 20;
  const uint32_t code0 = tiles[0];
  const bool kv0 = (code0 >> 8) == T_KV;
  const int c00 = kv0 ? 1024 + (code0 & 31) * 128 + rank * 64 : (code0 & 31) * 256 + rank * 128;
  const int rot0 = P.rot1[cl];
  const CUtensorMap* ma0 = (code0 >> 8) <= T_QB ? &P.x : &P.ckv;
  const CUtensorMap* mb0 = kv0 ? &P.wqkv : (code0 >> 8) == T_QB ? &P.wq : (code0 >> 8) == T_KB ? &P.wuk : &P.wuv;
  if (tid == 256) {
    tma_prefetch_desc(ma0);
    tma_prefetch_desc(mb0);
  } else if (tid == 0) {
#pragma unroll
    for (int s = 0; s < G_STAGES; s++) {
      mbar_init(sb + B_GFULL + 8 * s, 1);
      mbar_init(sb + B_GEMPTY + 8 * s, 4);
    }
    asm volatile("fence.mbarrier_init.release.cluster;" ::: "memory");
  } else if (tid == 32) {
    mbar_init(sb + B_SFULL, 8);
    mbar_init(sb + B_SFREE, 1);
    mbar_init(sb + B_WFULL, 1);
    mbar_init(sb + B_KFULL, 1);
    mbar_init(sb + B_KGO, 1);
    mbar_init(sb + B_P1DRAIN, 1);
    mbar_init(sb + B_P1DONE, 2);
    mbar_init(sb + B_P2DONE, 2);
    mbar_init(sb + B_ZGO, 1);
#pragma unroll
    for (int s = 0; s < 2; s++) {
      mbar_init(sb + B_QFULL + 8 * s, 1);
      mbar_init(sb + B_QEMPTY + 8 * s, 1);
      mbar_init(sb + B_OFULL + 8 * s, 8);
    }
    asm volatile("st.shared.u32 [%0], %1;" ::"r"(sb + B_PROG), "r"(0) : "memory");
    asm volatile("fence.mbarrier_init.release.cluster;" ::: "memory");
  } else if (tid == 64) {
#pragma unroll
    for (int s = 0; s < A_SLOTS; s++) {
      mbar_init(sb + B_AFULL + 8 * s, 1);
      mbar_init(sb + B_AEMPTY + 8 * s, 4);
    }
    asm volatile("fence.mbarrier_init.release.cluster;" ::: "memory");
  } else if (tid == 96) {
#pragma unroll
    for (int s = 0; s < O_STAGES; s++) {
      mbar_init(sb + B_OFULLS + 8 * s, 1);
      mbar_init(sb + B_OEMPTYS + 8 * s, 4);
    }
    asm volatile("fence.mbarrier_init.release.cluster;" ::: "memory");
  } else if (tid >= 128 && tid < 192) {
    asm volatile("st.shared.u32 [%0], %1;" ::"r"(sb + G_ONES_OFF + (tid - 128) * 4), "r"(0x3F803F80u) : "memory");
    fence_async_smem();
  }
  __syncthreads();
  asm volatile("barrier.cluster.arrive.relaxed.aligned;" ::: "memory");
  asm volatile("barrier.cluster.wait.aligned;" ::: "memory");
  if (warpid == 8) {
#pragma unroll 1
    for (int k = 0; k < G_STAGES; k++) {
      const int ps = (k + rot0) & (G_STAGES - 1);
      const uint32_t sa = sb + (ps >> 1) * 2 * G_STAGE_BYTES, sbb = sa + 16384 + (k & 1) * 16384 + rank * 8192;
      const uint32_t fb = sb + B_GFULL + 8 * ps;
      if (elect_one()) {
        mbar_expect_tx(fb, (k & 1) ? 16384 : 32768);
        if (!(k & 1)) tma_load(sa, ma0, k * 32, ((code0 >> 5) & 7) * 256 + rank * 128, fb);
        tma_load_mc(sbb, mb0, c00, k * 32, fb, 3);
        tma_load_mc(sbb + 4096, mb0, c00 + (kv0 ? 1024 : 64), k * 32, fb, 3);
      }
    }
  }
  __syncwarp();
  if (wgid == 2) {
    reg_dec<56>();
    const int warp = warpid, lane = tid & 31;
    uint32_t fin_ph = 0;
    if (warp == 8) {
      {
        int stage = rot0, hist = 0;
        uint32_t phase = 0;
#pragma unroll 1
        for (int it = 0; it < K1_MAXT; it++) {
          const uint32_t code = tiles[it];
          if (code == 0xFFFF) break;
          const int type = code >> 8, rp = (code >> 5) & 7, col = code & 31;
          const CUtensorMap* ma = (type <= T_QB) ? &P.x : &P.ckv;
          const CUtensorMap* mb = (type == T_KV || (type == T_QA && rank == 0)) ? &P.wqkv
                                  : (type <= T_QB)                              ? &P.wq
                                  : (type == T_KB)                              ? &P.wuk
                                                                                : &P.wuv;
          int c0, c1;
          if (type == T_KV) {
            c0 = 1024 + col * 128 + rank * 64;
            c1 = c0 + 1024;
          } else {
            c0 = (type == T_QA) ? col * 128 : col * 256 + rank * 128;
            c1 = c0 + 64;
          }
          const int nk = (type <= T_QB) ? 32 : 16;
          const int row0 = rp * 256 + rank * 128;
#pragma unroll 1
          for (int k = it ? 0 : G_STAGES; k < nk; k++) {
            const bool small = (type < T_QB && k >= 24) || (hist & 1) || ((hist & 2) && k <= 8);
            if (stage >= (small ? 6 : 8)) stage = 0;
            mbar_wait(sb + B_GEMPTY + 8 * stage, (phase >> stage) & 1);
            phase ^= 1u << stage;
            const uint32_t sa = sb + (stage >> 1) * 2 * G_STAGE_BYTES, sbb = sa + 16384 + (k & 1) * 16384 + rank * 8192;
            const uint32_t fb = sb + B_GFULL + 8 * stage;
            if (elect_one()) {
              if (k & 1) tma_load(sa, ma, (k - 1) * 32, row0, fb - 8);
              mbar_expect_tx(fb, (k & 1) ? 16384 : 32768);
              tma_load_mc(sbb, mb, c0, k * 32, fb, 3);
              tma_load_mc(sbb + 4096, mb, c1, k * 32, fb, 3);
            }
            if (k == 31 && type < T_QB) {
              mbar_wait(sb + B_GEMPTY + 8 * 7, (phase >> 7) & 1);
              if (elect_one()) {
                mbar_expect_tx(sb + B_WFULL, 8192);
                tma_load(sb + G_WPHI_OFF, &P.wphi, 0, col * 128, sb + B_WFULL);
                if (type == T_QA) mbar_arrive(sb + B_KGO);
              }
            }
            stage++;
          }
          hist = (hist << 1) | (type < T_QB);
        }
        tma_prefetch_desc(&P.qkv_ld);
        spin_until(&g_cnt[(C_HEAD + (items[0] >> 4)) * 32], 48);
        __syncwarp();
        int drained = 0;
        auto drain = [&](int n) {
#pragma unroll 1
          for (; drained < n; drained++) mbar_wait(sb + B_GEMPTY + 8 * drained, (phase >> drained) & 1);
        };
        drain(2);
        if (elect_one()) mbar_arrive(sb + B_P1DRAIN);
        int slot = 0, nld = 0, vrow = -1;
        uint32_t aph = 1;
        auto load_kv = [&](int row) {
          if (nld < 5) {
            drain(nld < 2 ? 4 : nld == 2 ? 6 : 8);
            if (nld == 4) mbar_wait(sb + B_P1DONE, 0);
            nld++;
          }
          mbar_wait(sb + B_AEMPTY + 8 * slot, aph);
          const uint32_t dst = sb + A_RING_OFF + slot * A_TILE, fb = sb + B_AFULL + 8 * slot;
          if (elect_one()) {
            if (row >= 0) {
              mbar_expect_tx(fb, A_TILE);
              tma_load_mc(dst + rank * 16384, &P.qkv_ld, 0, qkv_row(rank, row), fb, 3);
            } else {
              mbar_arrive(fb);
            }
          }
          if (++slot == A_SLOTS) { slot = 0; aph ^= 1; }
        };
#pragma unroll 1
        for (int it = 0; it < K2_MAXI; it++) {
          const uint32_t code = items[it];
          if (code == 0xFFFF) break;
          const int h = code >> 4, qt = code & 15;
          if (it > 0) spin_until(&g_cnt[(C_HEAD + h) * 32], 48);
          __syncwarp();
          asm volatile("fence.proxy.async;" ::: "memory");
          if (it == 1)
            for (int i = P.skip2[cl]; i > 0; i--) load_kv(-1);
#pragma unroll 1
          for (int j = 2 * qt + 1; j >= 0; j--) {
            load_kv((32 + h) * SEQ + j * 128);
            if (vrow >= 0) load_kv(vrow);
            vrow = (64 + h) * SEQ + j * 128;
          }
        }
        load_kv(vrow);
        fin_ph = aph;
        if (has_p3) {
          tma_prefetch_desc(&P.out_st);
          tma_prefetch_desc(&P.o_ld);
          tma_prefetch_desc(&P.wo);
          tma_prefetch_desc(&P.wob);
          int known = 0;
          stage = 0;
          phase = 0;
          int freed = 0;
#pragma unroll 1
          for (int k = 0; k < K3_NK; k++) {
            if (k < 6) {
#pragma unroll 1
              for (const int need = (k * 3 + 2) / 4 + 1; freed < need; freed++) mbar_wait(sb + B_AEMPTY + 8 * freed, aph);
              if (lane < 4) mbar_arrive_cluster(sb + B_OEMPTYS + 8 * k, lane & 1);
              __syncwarp();
            }
            const uint32_t sa = sb + A_RING_OFF + (stage >> 1) * 2 * G_STAGE_BYTES;
            const uint32_t sbb = sa + 16384 + (k & 1) * 16384 + rank * 8192, fb = sb + B_OFULLS + 8 * stage;
            mbar_wait(sb + B_OEMPTYS + 8 * stage, phase);
            const int kk = k3[k >> 2] * 4 + (k & 3);
            const CUtensorMap* mb = kk < 32 ? &P.wo : &P.wob;
            const int kr = (kk < 32 ? kk : kk - 32) * 32;
            if (elect_one()) {
              if (k == ZK) mbar_arrive(sb + B_ZGO);
              mbar_expect_tx(fb, (k & 1) ? 16384 : 32768);
              tma_load_mc(sbb, mb, ct3 * 256 + rank * 128, kr, fb, 3);
              tma_load_mc(sbb + 4096, mb, ct3 * 256 + rank * 128 + 64, kr, fb, 3);
            }
            if (k >= known) {
              uint32_t n = 0;
              do {
                asm volatile("ld.acquire.cta.shared.u32 %0, [%1];" : "=r"(known) : "r"(sb + B_PROG) : "memory");
                known = __shfl_sync(0xffffffffu, known, 0);
                asm volatile("{\n.reg .pred q;\n.reg .u64 z;\nmov.u64 z, 0;\nsetp.gt.u32 q, %0, 0x4000000;\n@q st.global.u32 [z], %0;\n}\n" ::"r"(++n));
              } while (k >= known);
              asm volatile("fence.proxy.async;" ::: "memory");
            }
            if ((k & 1) && elect_one()) {
              if (kk < 32)
                tma_load(sa, &P.o_ld, (kk - 1) * 32, rt3 * 128, fb - 8);
              else
                tma_load(sa, &P.qkv_ld, 0, ((kk - 32) >> 1) * SEQ + rt3 * 128, fb - 8);
            }
            if (++stage == O_STAGES) { stage = 0; phase ^= 1; }
          }
        }
      }
    } else if (warp == 9) {
      if (lane == 0) {
        uint32_t ph = 0;
#pragma unroll 1
        for (int it = 0; it < K1_MAXT; it++) {
          const uint32_t code = tiles[it];
          if (code == 0xFFFF) break;
          const int type = code >> 8, rp = (code >> 5) & 7, col = code & 31;
          if (type == T_KV) continue;
          const bool last = (it + 1 == K1_MAXT) || (tiles[it + 1] == 0xFFFF);
          const int row0 = rp * 256 + rank * 128;
          const int y = (type == T_QA) ? col * SEQ + row0 : ((type - T_QB) * 32 + col * 2 + 1) * SEQ + row0;
          mbar_wait(sb + B_SFULL, ph);
          ph ^= 1;
#pragma unroll 1
          for (int q = 0; q < 4; q++) {
            const long long t0 = clock64();
            tma_store(&P.qkv_st, stg + 32768 + q * 8192, 0, qkv_row(q >> 1, y + (q & 1) * 64));
            if (q < 3 && !last) pace(t0, PACE);
          }
          if (!last) {
            bulk_commit();
            bulk_wait_read<0>();
            mbar_arrive(sb + B_SFREE);
            if (type == T_QA) {
              bulk_wait<0>();
              red_release(&g_cnt[(C_HEAD + col) * 32], 1);
            }
            if (it + 2 < K1_MAXT) {
              const uint32_t n1 = tiles[it + 1], n2 = tiles[it + 2];
              const bool x2 = (n2 >> 8) <= T_QB;
              if (n2 != 0xFFFF && x2 != ((n1 >> 8) <= T_QB)) {
                const int r = ((n2 >> 5) & 7) * 256 + rank * 128 + ((cl >> 3) & 7) * 16;
                prefetch_l2(x2 ? (const char*)P.xin + r * 2048 : (const char*)P.ckv_p + r * 1024, x2 ? 32768 : 16384);
              }
            }
            mbar_wait(sb + B_SFULL, ph);
            ph ^= 1;
          }
#pragma unroll 1
          for (int q = 0; q < 4; q++) {
            const long long t0 = clock64();
            if (type == T_QA)
              tma_store(&P.o_st, stg + 32768 + q * 8192, col * 128 + (q >> 1) * 64, row0 + (q & 1) * 64);
            else
              tma_store(&P.qkv_st, stg + (last ? 0 : 32768) + q * 8192, 0, qkv_row(q >> 1, y - SEQ + (q & 1) * 64));
            if (q < 3 && !last && type != T_QA) pace(t0, PACE);
          }
          bulk_commit();
          bulk_wait_read<0>();
          if (last) {
            mbar_arrive_cluster(sb + B_P1DONE, 0);
            mbar_arrive_cluster(sb + B_P1DONE, 1);
          } else {
            mbar_arrive(sb + B_SFREE);
          }
          bulk_wait<0>();
          if (type != T_QA) {
            red_release(&g_cnt[(C_HEAD + col * 2) * 32], 1);
            asm volatile("red.relaxed.gpu.global.add.u32 [%0], 1;" ::"l"(&g_cnt[(C_HEAD + col * 2 + 1) * 32]) : "memory");
          } else {
            red_release(&g_cnt[(C_O + rp * 2 + rank) * 32], 1);
          }
        }
#pragma unroll 1
        for (int it = 0; it < K2_MAXI; it++) {
          const uint32_t code = items[it];
          if (code == 0xFFFF) break;
          const int h = code >> 4, qt = code & 15;
          const uint32_t src = sb + (it & 1) * A_Q_STRIDE;
          mbar_wait(sb + B_OFULL + 8 * (it & 1), (it >> 1) & 1);
#pragma unroll
          for (int q = 0; q < 4; q++)
            tma_store(&P.qkv_st, src + q * 8192, 0, (2 * h + (q >> 1)) * SEQ + qt * 256 + ((q & 1) ? 3 - rank : rank) * 64);
          bulk_commit();
          bulk_wait_read<0>();
          mbar_arrive(sb + B_QEMPTY + 8 * (it & 1));
          if (has_p3 && (it & 1) && (it + 2 >= K2_MAXI || items[it + 1] == 0xFFFF || items[it + 2] == 0xFFFF))
            for (int i = 0; i < 8; i++) mbar_arrive_cluster(sb + B_OEMPTYS + 8 * (6 + (i & 1)), (i >> 1) & 1);
          bulk_wait<0>();
          red_release(&g_cnt[(C_DONE + qt) * 32 + h], 1);
        }
        mbar_arrive(sb + B_P2DONE);
      }
    } else {
      const int hw = warp - 10;
      if (blockIdx.x < 128) {
        const int grp = blockIdx.x >> 4;
        helper_gate(P, (blockIdx.x & 15) * 128 + grp * 16, hw, lane);
        bar_sync(3, 64);
        if (hw == 0) {
          if (lane == 0) red_release(&g_cnt[(C_GATE + (blockIdx.x & 15)) * 32], 1);
          bar_sync(4, 288);
          if (lane == 0) {
            red_release(&g_cnt[(C_PART + grp) * 32], 1);
            spin_until(&g_cnt[(C_PART + grp) * 32], 16);
          }
        }
        bar_sync(3, 64);
        helper_reduce(blockIdx.x, hw, lane);
        bar_sync(3, 64);
        if (tid == 320) {
            red_release(&g_cnt[(C_KVT + grp) * 32], 1);
            spin_until(&g_cnt[(C_KVT + grp) * 32], 16);
            spin_until(&g_cnt[(C_GATE + (blockIdx.x & 15)) * 32], 8);
            asm volatile("fence.proxy.async;" ::: "memory");
            mbar_wait(sb + B_KGO, 0);
            mbar_expect_tx(sb + B_KFULL, 20480);
            asm volatile("cp.async.bulk.shared::cluster.global.mbarrier::complete_tx::bytes [%0], [%1], %2, [%3];" ::"r"(stg),
                         "l"(g_kvt + grp * 4 * 2560), "r"(20480), "r"(sb + B_KFULL)
                         : "memory");
        }
        __syncwarp();
      }
      if (hw == 0) {
        if (lane < 16) spin_until(&g_cnt[(C_GATE + lane) * 32], 8);
        __syncwarp();
#pragma unroll 1
        for (int it = 0; it < K2_MAXI && lane == 0; it++) {
          const uint32_t code = items[it];
          if (code == 0xFFFF) break;
          const int h = code >> 4, qt = code & 15, b = it & 1;
          spin_until(&g_cnt[(C_HEAD + h) * 32], 48);
          asm volatile("fence.proxy.async;" ::: "memory");
          if (it < 2) mbar_wait(sb + (it == 0 ? B_P1DRAIN : B_P1DONE), 0);
          mbar_wait(sb + B_QEMPTY + 8 * b, ((it >> 1) & 1) ^ 1);
          const uint32_t dst = sb + b * A_Q_STRIDE, fb = sb + B_QFULL + 8 * b;
          mbar_expect_tx(fb, A_TILE);
#pragma unroll
          for (int q = 0; q < 4; q++)
            tma_load(dst + q * 8192, &P.qkv_st, 0, (2 * h + (q >> 1)) * SEQ + qt * 256 + ((q & 1) ? 3 - rank : rank) * 64, fb);
        }
      } else {
        int togo = 0;
#pragma unroll 1
        for (int it = 0; it < K2_MAXI && items[it] != 0xFFFF; it++) togo += 2 * (items[it] & 15) + 2;
#pragma unroll 1
        for (int it = 0; togo - 2 * (items[it] & 15) - 2 >= PF3_TILES; it++) {
          togo -= 2 * (items[it] & 15) + 2;
          mbar_wait(sb + B_OFULL + 8 * (it & 1), (it >> 1) & 1);
        }
        if (lane == 0) {
#pragma unroll 1
          for (int i = blockIdx.x; i < PF3_N * 32; i += 132) {
            const int b = P.k3[4][((i >> 4) & 1) * 20 + (i >> 5)], o = (i & 15) * 16384;
            prefetch_l2(b < 8 ? (const char*)P.wo_p + b * 262144 + o : (const char*)P.wob_p + (size_t)(b - 8) * 262144 + o, 16384);
            __nanosleep(500);
          }
        }
        __syncwarp();
        if (has_p3) {
          if (lane == 0) {
            spin_until(&g_cnt[(C_O + rt3) * 32], 8);
            asm volatile("fence.proxy.async;" ::: "memory");
            const int b = k3[ct3 >> 1];
            tma_prefetch_l2(&P.o_ld, b * 128 + (ct3 & 1) * 64, rt3 * 128);
          }
          __syncwarp();
          const int b0 = k3[lane < 20 ? lane : 0];
          uint32_t n = 99, it = 0;
          while (true) {
            const unsigned done = __ballot_sync(0xffffffffu, ld_acquire(&g_cnt[(C_DONE + (rt3 >> 1)) * 32 + lane]) >= 2);
            const unsigned m0 = __ballot_sync(0xffffffffu, lane < 20 && (b0 < 8 || ((done >> (b0 - 8)) & 1)));
            const uint32_t c = __ffs(~m0) - 1;
            if (c != n && lane == 0)
              asm volatile("st.release.cta.shared.u32 [%0], %1;" ::"r"(sb + B_PROG), "r"(4 * c) : "memory");
            n = c;
            if (n == 20 || ++it > (1u << 20)) break;
            __nanosleep(500);
          }
          mbar_wait(sb + B_ZGO, 0);
          __nv_bfloat16* zp = P.out + (size_t)(rt3 * 128 + (lane >> 4)) * 1024 + ct3 * 256 + kh3 * 128 + (lane & 15) * 8;
#pragma unroll 4
          for (int i = 0; i < 64; i++) *(uint4*)(zp + i * 2048) = make_uint4(0, 0, 0, 0);
          __syncwarp();
          if (lane == 0) {
            red_release(&g_cnt[(C_ZERO + rt3) * 32 + ct3], 1);
            spin_until(&g_cnt[(C_ZERO + rt3) * 32 + ct3], 2);
            mbar_arrive(sb + B_P2DONE);
          }
        }
      }
    }
    __syncwarp();
    bar_sync(7, 128);
    if (warp == 10) {
      unsigned ticket = 0;
      if (lane == 0) asm volatile("atom.acq_rel.gpu.global.add.u32 %0, [%1], 1;" : "=r"(ticket) : "l"(&g_cnt[C_FIN * 32]) : "memory");
      ticket = __shfl_sync(0xffffffffu, ticket, 0);
      if (ticket == gridDim.x - 1)
        for (int i = 0; i < C_LINES; i++) g_cnt[i * 32 + lane] = 0;
    } else if (tid == 256) {
      if (has_p3)
        mbar_wait(sb + B_OEMPTYS + 8 * (O_STAGES - 1), (K3_NK / O_STAGES) & 1);
      else
        mbar_wait(sb + B_AEMPTY + 8 * (A_SLOTS - 1), fin_ph);
    }
  } else {
    reg_inc<224>();
    const int wg = wgid, t128 = tid & 127, warp = t128 >> 5, lane = tid & 31;
#pragma unroll 1
    for (int pass = 0;; pass++) {
      {
      K1Ctx ctx;
      ctx.sb = sb;
      ctx.rank = rank;
      ctx.wg = wg;
      ctx.t128 = t128;
      ctx.full = sb + (pass ? B_OFULLS : B_GFULL);
      ctx.empty = sb + (pass ? B_OEMPTYS : B_GEMPTY);
      ctx.st = pass ? 0 : rot0 * 8;
      ctx.lim = 64;
      ctx.phases = ctx.pend = ctx.npend = 0;
      ctx.alo0 = (uint32_t)make_desc(sb + (pass ? A_RING_OFF : 0) + wg * 8192, 16, 1024);
      ctx.alo = ctx.alo0 + ctx.st * 192;
      ctx.blo = (uint32_t)make_desc(sb + (pass ? A_RING_OFF : 0) + 16384, 4096, 1024) + ctx.st * 192;
      const uint32_t sfull = sb + B_SFULL, sfree = sb + B_SFREE;
      const uint32_t ra = (pass ? sb : stg) + (wg * 64 + warp * 16 + (lane & 7) + ((lane >> 3) & 1) * 8) * 128;
      const int hold = pass ? HOLD : HOLD1;
      uint32_t sph = 0, wph = 0;
      bool stored = false;
      uint32_t pcode = 0xFFFF;
      float acc[128];
      uint32_t pk[64];
#pragma unroll
      for (int i = 0; i < 64; i++) asm volatile("mov.u32 %0, 0;" : "=r"(pk[i]));
      auto out_add = [&](int q0) {
        fence_async_smem();
        __syncwarp();
        if (lane == 0) {
#pragma unroll
          for (int q = q0; q < q0 + 2; q++)
            asm volatile("cp.reduce.async.bulk.tensor.2d.global.shared::cta.add.bulk_group [%0, {%2, %3}], [%1];" ::"l"(&P.out_st),
                         "r"(ra + q * 16384), "r"(ct3 * 256 + q * 64), "r"(rt3 * 128 + wg * 64 + warp * 16)
                         : "memory");
        }
      };
      auto stage_lo = [&](uint32_t dst) {
#pragma unroll
        for (int i = 0; i < 8; i++)
          stsm4(dst + (i >> 2) * 16384 + (((uint32_t)(2 * (i & 3) + (lane >> 4)) ^ (lane & 7)) << 4), pk[4 * i], pk[4 * i + 1],
                pk[4 * i + 2], pk[4 * i + 3]);
      };
      auto stage_hi = [&]() {
        if (stored) {
          mbar_wait(sfree, sph);
          sph ^= 1;
        }
#pragma unroll
        for (int i = 8; i < 16; i++)
          stsm4(ra + (i >> 2) * 16384 + (((uint32_t)(2 * (i & 3) + (lane >> 4)) ^ (lane & 7)) << 4), pk[4 * i], pk[4 * i + 1],
                pk[4 * i + 2], pk[4 * i + 3]);
      };
      auto staged = [&](bool signal) {
        fence_async_smem();
        __syncwarp();
        if (signal && lane == 0) mbar_arrive(sfull);
      };
      k1_wait(ctx);
      uint32_t code = pass ? T_OUT << 8 : code0;
      for (int it = 0;; it++) {
        int left = pass ? K3_NK - 2 : ((code >> 8) <= T_QB) ? 30 : 14;
        const int ptype = pcode >> 8;
        k1_big<true, false>(acc, ctx);
        if (it > 0) stage_hi();
        k1_big<false>(acc, ctx);
        wg_wait<1>();
        k1_rel(ctx);
        if (ptype == T_KV) {
          mbar_wait(sb + B_WFULL, wph);
          wph ^= 1;
          stage_lo(ra);
        } else if (it > 0) {
          staged(true);
        }
        stored = it > 0 && ptype != T_KV;
        if (ptype == T_KV) {
          staged(false);
#pragma unroll 1
          for (int idx = 0; idx < 2; idx++) k1_kv_pair(acc, ctx, pcode, idx);
          bar_arrive(4, 288);
          left -= 14;
        } else if (it > 0) {
#pragma unroll 1
          for (int i = 0; i < 7; i++) {
            if (i == 6 && ptype != T_QA) ctx.lim = 64;
            k1_big<false>(acc, ctx);
            wg_wait<1>();
            k1_rel(ctx);
          }
          mbar_wait(sfree, sph);
          sph ^= 1;
          stage_lo(ra + 32768);
          k1_big<false>(acc, ctx);
          wg_wait<1>();
          k1_rel(ctx);
          staged(ptype != T_QA);
          left -= 8;
          if (ptype == T_QA) {
            mbar_wait(sb + B_WFULL, wph);
            wph ^= 1;
            mbar_wait(sb + B_KFULL, 0);
            const int grow = ((pcode >> 5) & 7) * 256 + rank * 128 + wg * 64 + warp * 16 + (lane >> 2);
            const float g0 = __ldcg(g_gate + grow), g1 = __ldcg(g_gate + grow + 8);
#pragma unroll 1
            for (int idx = 0; idx < 4; idx++) k1_q_head(acc, ctx, idx, g0, g1);
            staged(true);
            left -= 20;
          }
        }
        const int shrink = (code >> 8) < T_QB ? 9 : -1;
        const bool do_hold = left >= hold && hold > 0;
#pragma unroll 1
        for (; left > 0; left--) {
          if (left == hold && wg) bar_sync(8, 256);
          if (left == shrink) ctx.lim = 48;
          k1_big<false>(acc, ctx);
          wg_wait<1>();
          k1_rel(ctx);
        }
        if (do_hold && wg == 0) bar_arrive(8, 256);
        pcode = code;
        code = !pass && it + 1 < K1_MAXT ? tiles[it + 1] : 0xFFFFu;
        if (code != 0xFFFF) k1_wait(ctx);
        if (pass) {
          mbar_wait(sb + B_P2DONE, 0);
          if (lane == 0) asm volatile("fence.proxy.async.global;" ::: "memory");
        }
        wg_wait<0>();
        reg_fence(acc);
#pragma unroll
        for (int i = 0; i < 64; i++) pk[i] = pack_bf16(acc[2 * i], acc[2 * i + 1]);
        k1_rel(ctx);
        if (code == 0xFFFF) break;
      }
      const uint32_t xs = pass ? 1 : 7;
      if (pass) {
        stage_lo(ra);
        out_add(0);
        mbar_wait(ctx.empty + 8 * xs, (ctx.phases >> (4 * xs)) & 1);
        stage_hi();
        out_add(2);
        if (lane == 0) {
          bulk_commit();
          bulk_wait_read<0>();
        }
      } else {
        stage_hi();
        mbar_wait(ctx.empty + 8 * xs, ((ctx.phases >> (4 * xs)) & 1) ^ 1);
        stage_lo(ra);
        staged(true);
      }
      }
      if (pass) break;
      const int rloc = wg * 64 + warp * 16;
      const int rblk = (wg ? 3 - rank : rank) * 64 + warp * 16 + (lane >> 2);
      const bool up = (wg ^ rank) == 0;
      const uint64_t qdesc0 = make_desc(sb + wg * 8192, 16, 1024);
      float S[64], O[64];
      uint32_t Pr[32];
#pragma unroll
      for (int i = 0; i < 64; i++) O[i] = 0.f;
#pragma unroll
      for (int i = 0; i < 32; i++) Pr[i] = 0;
      float m0, m1, l0 = 0.f, l1 = 0.f;
      uint32_t code = 0;
      int accum = 0;
      AttnCtx c = {make_desc(sb + A_RING_OFF, 16, 1024), make_desc(sb + A_RING_OFF, 16384, 1024), sb + B_AFULL, sb + B_AEMPTY,
                   sb + B_PIN, P.zero, 0, 0, wg, lane, t128};
      if (wg == 1) bar_arrive(5, 256);
      mbar_wait(sb + B_AFULL, 0);
#pragma unroll 1
      for (int it = 0;; it++) {
        const uint32_t ncode = it < K2_MAXI ? items[it] : 0xFFFFu;
        const bool fin = ncode == 0xFFFF;
        const uint64_t qdesc = qdesc0 + (it & 1) * (A_Q_STRIDE >> 4);
        bool epi = it > 0;
        if (it == 1) {
          for (int i = P.skip2[cl]; i > 0; i--) {
            bar_sync(1 + wg, 128);
            attn_release(c.empty0 + 8 * c.slot, t128);
            attn_next(c);
            mbar_wait(c.full0 + 8 * c.slot, c.phase);
          }
        }
        AttnOut o;
        o.l0 = l0;
        o.l1 = l1;
        o.g0 = epi ? __ldcg(g_gate + (code & 15) * 256 + rblk) : 0.f;
        o.g1 = epi ? __ldcg(g_gate + (code & 15) * 256 + rblk + 8) : 0.f;
        o.stage = sb + ((it & 1) ^ 1) * A_Q_STRIDE + rloc * 128;
        o.ofull = sb + B_OFULL + 8 * ((it & 1) ^ 1);
        if (fin || wg == 0) {
          if (!fin) {
            attn_release(c.empty0 + 8 * c.slot, t128);
            attn_next(c);
          }
          if (epi) {
            mbar_wait(c.full0 + 8 * c.slot, c.phase);
            bar_sync(5 + wg, 256);
            reg_fence(O);
            reg_fence_u(Pr);
            wg_fence();
            attn_pv<8>(O, Pr, c.vdesc0 + c.slot * 2048, accum);
            wg_commit();
            if (wg == 0) bar_arrive(6, 256);
            wg_wait<0>();
            reg_fence(O);
            attn_release(c.empty0 + 8 * c.slot, t128);
            attn_next(c);
            attn_epilogue(O, o.l0, o.l1, o.g0, o.g1, o.stage, o.ofull, lane);
            if (fin) break;
            epi = false;
          } else {
            bar_sync(5, 256);
            bar_arrive(6, 256);
          }
          mbar_wait(c.full0 + 8 * c.slot, c.phase);
        }
        mbar_wait(sb + B_QFULL + 8 * (it & 1), (it >> 1) & 1);
        if (wg == 0) {
          if (up)
            attn_step_first<true, false>(S, O, Pr, m0, m1, l0, l1, c, qdesc, epi, accum, rblk & 127);
          else
            attn_step_first<false, false>(S, O, Pr, m0, m1, l0, l1, c, qdesc, epi, accum, rblk & 127);
        } else {
          if (up)
            attn_step_first<true, true>(S, O, Pr, m0, m1, l0, l1, c, qdesc, epi, accum, rblk & 127);
          else
            attn_step_first<false, true>(S, O, Pr, m0, m1, l0, l1, c, qdesc, epi, accum, rblk & 127);
        }
        accum = 0;
#pragma unroll 1
        for (int j = (ncode & 15) * 2 + wg; j > 0; j--) {
          attn_step(S, O, Pr, m0, m1, l0, l1, c, qdesc, accum, epi, o);
          accum = 1;
          epi = false;
        }
        code = ncode;
      }
      if (!has_p3) break;
    }
  }
}

typedef CUresult (*EncodeFn)(CUtensorMap*, CUtensorMapDataType, cuuint32_t, void*, const cuuint64_t*, const cuuint64_t*,
                             const cuuint32_t*, const cuuint32_t*, CUtensorMapInterleave, CUtensorMapSwizzle,
                             CUtensorMapL2promotion, CUtensorMapFloatOOBfill);

static void make_map(EncodeFn enc, CUtensorMap* m, const void* ptr, uint64_t cols, uint64_t rows, uint32_t box_rows,
                     uint32_t box_cols = 64) {
  cuuint64_t dims[2] = {cols, rows};
  cuuint64_t strides[1] = {cols * 2};
  cuuint32_t box[2] = {box_cols, box_rows};
  cuuint32_t es[2] = {1, 1};
  enc(m, CU_TENSOR_MAP_DATA_TYPE_BFLOAT16, 2, const_cast<void*>(ptr), dims, strides, box, es, CU_TENSOR_MAP_INTERLEAVE_NONE,
      box_cols == 64 ? CU_TENSOR_MAP_SWIZZLE_128B : CU_TENSOR_MAP_SWIZZLE_64B, CU_TENSOR_MAP_L2_PROMOTION_L2_256B,
      CU_TENSOR_MAP_FLOAT_OOB_FILL_NONE);
}

extern "C" void kernel_launch(void* const* d_in, const int* in_sizes, int n_in, void* d_out, int out_size) {
  static EncodeFn enc = nullptr;
  static void *p_qkv, *p_o;
  if (!enc) {
    void* fn = nullptr;
    cudaDriverEntryPointQueryResult qr;
    cudaGetDriverEntryPoint("cuTensorMapEncodeTiled", &fn, cudaEnableDefault, &qr);
    enc = (EncodeFn)fn;
    cudaGetSymbolAddress(&p_qkv, g_qkv);
    cudaGetSymbolAddress(&p_o, g_o);
    cudaFuncSetAttribute(gated_mix_kernel, cudaFuncAttributeMaxDynamicSharedMemorySize, SMEM_BYTES);
  }
  static Params p;
  make_map(enc, &p.x, d_in[0], 1024, SEQ, 128);
  make_map(enc, &p.ckv, d_in[5], 512, SEQ, 128);
  make_map(enc, &p.wqkv, d_in[1], 3072, 1024, 32);
  make_map(enc, &p.wq, d_in[6], 4096, 1024, 32);
  make_map(enc, &p.wuk, d_in[7], 4096, 512, 32);
  make_map(enc, &p.wuv, d_in[8], 4096, 512, 32);
  make_map(enc, &p.wphi, d_in[2], 32, 1024, 128, 32);
  make_map(enc, &p.qkv_st, p_qkv, 64, 192 * SEQ, 64);
  make_map(enc, &p.o_st, p_o, 1024, SEQ, 64);
  make_map(enc, &p.qkv_ld, p_qkv, 64, 192 * SEQ, 128);
  make_map(enc, &p.o_ld, p_o, 1024, SEQ, 128);
  make_map(enc, &p.wo, d_in[3], 1024, 1024, 32);
  make_map(enc, &p.wob, d_in[9], 1024, 4096, 32);
  make_map(enc, &p.out_st, d_out, 1024, SEQ, 16);
  for (int i = 0; i < 66; i++)
    for (int j = 0; j < K1_MAXT; j++) p.tiles[i][j] = c_tiles[i][j];
  for (int i = 0; i < 66; i++)
    for (int j = 0; j < K2_MAXI; j++) p.items[i][j] = c_items[i][j];
  for (int i = 0; i < 66; i++) p.rot1[i] = c_rot1[i];
  for (int i = 0; i < 66; i++) {
    int n = 0;
    for (int j = 0; j < K2_MAXI && c_items[i][j] != 0xFFFF; j++) n += 4 * ((c_items[i][j] & 15) + 1);
    p.skip2[i] = (A_SLOTS - n % A_SLOTS) % A_SLOTS;
  }
  for (int i = 0; i < 320; i++) p.k3[i / 40][i % 40] = c_k3[i / 40][i % 40];
  p.ckv_p = d_in[5];
  p.wo_p = d_in[3];
  p.wob_p = d_in[9];
  p.out = (__nv_bfloat16*)d_out;
  p.zero = 0;
  p.xin = (const __nv_bfloat16*)d_in[0];
  p.gatew = (const __nv_bfloat16*)d_in[10];
  gated_mix_kernel<<<132, 384, SMEM_BYTES, cudaStreamPerThread>>>(p);
}
```
